```python
import torch

def _softmax(x, axis=-1):
    return torch.softmax(x, dim=axis)
def _gelu(x):
    return torch.nn.functional.gelu(x, approximate="tanh")
def _silu(x):
    return torch.nn.functional.silu(x)
def _sigmoid(x):
    return torch.sigmoid(x)
def _layernorm(x, axis=-1, eps=1e-5):
    m = x.mean(dim=axis, keepdim=True)
    v = x.var(dim=axis, keepdim=True, unbiased=False)
    return (x - m) / torch.sqrt(v + eps)
def _scatter_add(tgt, idx, src, axis=0):
    return tgt.clone().index_add_(axis, idx, src)
def _segment_sum(src, seg, n):
    out = torch.zeros((n,) + src.shape[1:], dtype=src.dtype)
    return out.index_add_(0, seg, src)
def _pad(x, pw):
    flat = tuple(v for pair in reversed(pw) for v in pair)
    return torch.nn.functional.pad(x, flat)

kernel_name = 'sequential_preLN__compressed_kv_cla__mixer_s_mlp__prompt'

def setup_inputs():

    _w = (lambda a: (lambda t: t.to(torch.bfloat16) if t.is_floating_point() else t)(torch.as_tensor(a)))
    def _A_setup():
        B, H, Sq, Sk, D, M = 1, 32, 2048, 2048, 128, 512
        Dc = 4 * D
        return {
            "x": _w((lambda *s: torch.randn(*s, dtype=torch.bfloat16) * 0.1)(B, Sq, M)),
            "c_kv": _w((lambda *s: torch.randn(*s, dtype=torch.bfloat16) * 0.8)(B, Sk, Dc)),
            "w_q": _w((lambda *s: torch.randn(*s, dtype=torch.bfloat16) * 1.6)(M, H, D) * (M ** -0.5)),
            "w_uk": _w((lambda *s: torch.randn(*s, dtype=torch.bfloat16) * 1.6)(Dc, H, D) * (Dc ** -0.5)),
            "w_uv": _w((lambda *s: torch.randn(*s, dtype=torch.bfloat16) * 0.8)(Dc, H, D) * (Dc ** -0.5)),
            "w_o": _w((lambda *s: torch.randn(*s, dtype=torch.bfloat16) * 0.8)(H, D, M) * ((H * D) ** -0.5)),
        }
    _A_in = _A_setup()

    def _B_setup():
        B, S, D, F = 1, 2048, 512, 1792
        return {
            "x":  _w((lambda *s: torch.randn(*s, dtype=torch.bfloat16) * 0.1)(B, S, D)),
            "w1": _w((lambda *s: torch.randn(*s, dtype=torch.bfloat16) * 3.2)(D, D) * (D ** -0.5)),
            "w2": _w((lambda *s: torch.randn(*s, dtype=torch.bfloat16) * 3.2)(D, D) * (D ** -0.5)),
            "w3": _w((lambda *s: torch.randn(*s, dtype=torch.bfloat16) * 3.2)(D, F) * (D ** -0.5)),
            "w4": _w((lambda *s: torch.randn(*s, dtype=torch.bfloat16) * 3.2)(F, D) * (F ** -0.5)),
        }
    _B_in = _B_setup()

    return {
        "A_x": _A_in["x"],
        "A_c_kv": _A_in["c_kv"],
        "A_w_q": _A_in["w_q"],
        "A_w_uk": _A_in["w_uk"],
        "A_w_uv": _A_in["w_uv"],
        "A_w_o": _A_in["w_o"],
        "B_x": _B_in["x"],
        "B_w1": _B_in["w1"],
        "B_w2": _B_in["w2"],
        "B_w3": _B_in["w3"],
        "B_w4": _B_in["w4"],
    }

def reference(A_x, A_c_kv, A_w_q, A_w_uk, A_w_uv, A_w_o, B_x, B_w1, B_w2, B_w3, B_w4):
    def _A_ref(x, c_kv, w_q, w_uk, w_uv, w_o):
        B, Sq, M = x.shape[0], x.shape[1], x.shape[2]
        Sk = c_kv.shape[1]
        H, D = w_q.shape[1], w_q.shape[2]
        q = torch.einsum("bqm,mhd->bhqd", x, w_q)
        k = torch.einsum("bkc,chd->bhkd", c_kv, w_uk)
        v = torch.einsum("bkc,chd->bhkd", c_kv, w_uv)
        scores = torch.einsum("bhqd,bhkd->bhqk", q, k) * (D ** -0.5)
        off = Sk - Sq
        qi = torch.arange(Sq)[:, None]
        kj = torch.arange(Sk)[None, :]
        cmask = kj <= (qi + off)
        scores = torch.where(cmask[None, None], scores, -1e9)
        p = _softmax(scores, axis=-1)
        ctx = torch.einsum("bhqk,bhkd->bhqd", p, v)
        return torch.einsum("bhqd,hdm->bqm", ctx, w_o)

    def _B_ref(x, w1, w2, w3, w4):
        B, S, D = x.shape
        h = _gelu(_layernorm(x, axis=-1) @ w1)
        c = D // 4
        g0 = _pad(h[:, :, 0*c:1*c], ((0, 0), (1, 0), (0, 0)))[:, :S, :]
        g1 = _pad(h[:, :, 1*c:2*c], ((0, 0), (0, 1), (0, 0)))[:, 1:, :]
        g2 = _pad(h[:, :, 2*c:3*c], ((0, 0), (2, 0), (0, 0)))[:, :S, :]
        g3 = _pad(h[:, :, 3*c:   ], ((0, 0), (0, 2), (0, 0)))[:, 2:, :]
        hs = torch.concatenate([g0, g1, g2, g3], axis=-1) @ w2
        x1 = x + hs
        h2 = _gelu(_layernorm(x1, axis=-1) @ w3) @ w4
        return x1 + h2

    x = A_x
    h = x + _A_ref(_layernorm(x, axis=-1), A_c_kv, A_w_q, A_w_uk, A_w_uv, A_w_o)
    h2 = h + _B_ref(_layernorm(h, axis=-1), B_w1, B_w2, B_w3, B_w4)
    return h2
```

```cpp
#include <cuda_runtime.h>
#include <cuda_bf16.h>
#include <cuda.h>
#include <stdint.h>

typedef __nv_bfloat16 bf16;

constexpr int SEQ = 2048;
constexpr int DM = 512;
constexpr int NH = 32;
constexpr int HD = 128;
constexpr int FF = 1792;
#define USE_PDL true

__device__ __align__(1024) bf16  g_xn[SEQ * DM];
__device__ __align__(1024) bf16  g_kv[2 * NH * SEQ * HD];
#define NBUF 1
__device__ __align__(1024) bf16  g_hp[NBUF * SEQ * DM];
__device__ __align__(1024) bf16  g_h[SEQ * DM];
__device__ __align__(1024) bf16  g_y[SEQ * DM];
__device__ __align__(1024) bf16  g_h1[SEQ * DM];
__device__ __align__(1024) bf16  g_x1[SEQ * DM];
__device__ __align__(1024) bf16  g_g[SEQ * FF];
__device__ __align__(1024) float2 g_st[SEQ * 8];
__device__ __align__(1024) float g_cs3[FF];
__device__ unsigned int g_cnth[SEQ / 64];
__device__ __align__(1024) float g_nrm[2 * NH * 128];

#define TS(k, i) do {} while (0)
#define TSX(k, i) do {} while (0)
#define TS_DECL
#define TS_OUT(k) do {} while (0)
#define CYC_DECL
#define CYC_START do {} while (0)
#define CYC(i) do {} while (0)
#define CYC_N() do {} while (0)
#define CY2_DECL
#define CY2(i, stmt) do { stmt; } while (0)
#define CY2_OUT(w) do {} while (0)
#define CYC_OUT(w) do {} while (0)
__device__ __forceinline__ uint32_t smem_u32(const void* p) { return (uint32_t)__cvta_generic_to_shared(p); }
__device__ __forceinline__ void mbar_init(uint32_t bar, uint32_t cnt) {
  asm volatile("mbarrier.init.shared::cta.b64 [%0], %1;" ::"r"(bar), "r"(cnt) : "memory");
}
__device__ __forceinline__ void mbar_expect_tx(uint32_t bar, uint32_t bytes) {
  asm volatile("mbarrier.arrive.expect_tx.shared::cta.b64 _, [%0], %1;" ::"r"(bar), "r"(bytes) : "memory");
}
__device__ __forceinline__ void mbar_arrive(uint32_t bar) {
  asm volatile("mbarrier.arrive.shared::cta.b64 _, [%0];" ::"r"(bar) : "memory");
}
__device__ __forceinline__ void mbar_arrive_remote(uint32_t bar, uint32_t cta) {
  asm volatile("{\n.reg .b32 ra;\nmapa.shared::cluster.u32 ra, %0, %1;\nmbarrier.arrive.shared::cluster.b64 _, [ra];\n}"
               ::"r"(bar), "r"(cta) : "memory");
}
__device__ __forceinline__ void mbar_wait(uint32_t bar, uint32_t parity) {
  asm volatile(
      "{\n.reg .pred p;\n.reg .u32 c;\n"
      "mov.u32 c, 0;\n"
      "WAIT_LOOP:\n"
      "mbarrier.try_wait.parity.shared::cta.b64 p, [%0], %1;\n"
      "@p bra WAIT_DONE;\n"
      "add.u32 c, c, 1;\n"
      "setp.lt.u32 p, c, 0x1000000;\n"
      "@p bra WAIT_LOOP;\n"
      "trap;\n"
      "WAIT_DONE:\n}"
      ::"r"(bar), "r"(parity) : "memory");
}
__device__ __forceinline__ void tma_load_2d(uint32_t dst, const CUtensorMap* tm, int c0, int c1, uint32_t bar) {
  asm volatile("cp.async.bulk.tensor.2d.shared::cluster.global.mbarrier::complete_tx::bytes [%0], [%1, {%3, %4}], [%2];"
               ::"r"(dst), "l"(tm), "r"(bar), "r"(c0), "r"(c1) : "memory");
}
__device__ __forceinline__ void tma_load_2d_mc(uint32_t dst, const CUtensorMap* tm, int c0, int c1, uint32_t bar, uint16_t mask) {
  asm volatile("cp.async.bulk.tensor.2d.shared::cluster.global.mbarrier::complete_tx::bytes.multicast::cluster [%0], [%1, {%3, %4}], [%2], %5;"
               ::"r"(dst), "l"(tm), "r"(bar), "r"(c0), "r"(c1), "h"(mask) : "memory");
}
__device__ __forceinline__ void tma_load_4d(uint32_t dst, const CUtensorMap* tm, int c0, int c1, int c2, int c3, uint32_t bar) {
  asm volatile("cp.async.bulk.tensor.4d.shared::cluster.global.mbarrier::complete_tx::bytes [%0], [%1, {%3, %4, %5, %6}], [%2];"
               ::"r"(dst), "l"(tm), "r"(bar), "r"(c0), "r"(c1), "r"(c2), "r"(c3) : "memory");
}
__device__ __forceinline__ void tma_load_3d_mc(uint32_t dst, const CUtensorMap* tm, int c0, int c1, int c2, uint32_t bar, uint16_t mask) {
  asm volatile("cp.async.bulk.tensor.3d.shared::cluster.global.mbarrier::complete_tx::bytes.multicast::cluster [%0], [%1, {%3, %4, %5}], [%2], %6;"
               ::"r"(dst), "l"(tm), "r"(bar), "r"(c0), "r"(c1), "r"(c2), "h"(mask) : "memory");
}
__device__ __forceinline__ uint64_t policy_evict_first() {
  uint64_t p;
  asm volatile("createpolicy.fractional.L2::evict_unchanged.b64 %0, 1.0;" : "=l"(p));
  return p;
}
__device__ __forceinline__ void tma_load_2d_ef(uint32_t dst, const CUtensorMap* tm, int c0, int c1, uint32_t bar, uint64_t pol) {
  asm volatile("cp.async.bulk.tensor.2d.shared::cluster.global.mbarrier::complete_tx::bytes.L2::cache_hint [%0], [%1, {%3, %4}], [%2], %5;"
               ::"r"(dst), "l"(tm), "r"(bar), "r"(c0), "r"(c1), "l"(pol) : "memory");
}
__device__ __forceinline__ void tma_load_2d_mc_ef(uint32_t dst, const CUtensorMap* tm, int c0, int c1, uint32_t bar, uint16_t mask, uint64_t pol) {
  asm volatile("cp.async.bulk.tensor.2d.shared::cluster.global.mbarrier::complete_tx::bytes.multicast::cluster.L2::cache_hint [%0], [%1, {%3, %4}], [%2], %5, %6;"
               ::"r"(dst), "l"(tm), "r"(bar), "r"(c0), "r"(c1), "h"(mask), "l"(pol) : "memory");
}
__device__ __forceinline__ void tma_store_2d(const CUtensorMap* tm, uint32_t src, int c0, int c1) {
  asm volatile("cp.async.bulk.tensor.2d.global.shared::cta.bulk_group [%0, {%2, %3}], [%1];"
               ::"l"(tm), "r"(src), "r"(c0), "r"(c1) : "memory");
}
__device__ __forceinline__ void tma_red_add_2d(const CUtensorMap* tm, uint32_t src, int c0, int c1) {
  asm volatile("cp.reduce.async.bulk.tensor.2d.global.shared::cta.add.tile.bulk_group [%0, {%2, %3}], [%1];"
               ::"l"(tm), "r"(src), "r"(c0), "r"(c1) : "memory");
}
__device__ __forceinline__ void tma_prefetch_2d(const CUtensorMap* tm, int c0, int c1) {
  asm volatile("cp.async.bulk.prefetch.tensor.2d.L2.global [%0, {%1, %2}];" ::"l"(tm), "r"(c0), "r"(c1) : "memory");
}
__device__ __forceinline__ void bulk_prefetch(const void* p, uint32_t bytes) {
  asm volatile("cp.async.bulk.prefetch.L2.global [%0], %1;" ::"l"(p), "r"(bytes) : "memory");
}
__device__ __forceinline__ void bulk_commit() { asm volatile("cp.async.bulk.commit_group;" ::: "memory"); }
template <int N> __device__ __forceinline__ void bulk_wait_read() { asm volatile("cp.async.bulk.wait_group.read %0;" ::"n"(N) : "memory"); }
template <int N> __device__ __forceinline__ void bulk_wait() { asm volatile("cp.async.bulk.wait_group %0;" ::"n"(N) : "memory"); }
__device__ __forceinline__ void fence_async_smem() { asm volatile("fence.proxy.async.shared::cta;" ::: "memory"); }
__device__ __forceinline__ void prefetch_tmap(const CUtensorMap* tm) { asm volatile("prefetch.tensormap [%0];" ::"l"(tm) : "memory"); }
__device__ __forceinline__ void cluster_arrive() { asm volatile("barrier.cluster.arrive.relaxed.aligned;" ::: "memory"); }
__device__ __forceinline__ void cluster_wait() { asm volatile("barrier.cluster.wait.aligned;" ::: "memory"); }
__device__ __forceinline__ void cluster_sync_all() { cluster_arrive(); cluster_wait(); }
__device__ __forceinline__ void named_sync(int id, int n) { asm volatile("bar.sync %0, %1;" ::"r"(id), "r"(n) : "memory"); }
__device__ __forceinline__ void named_arrive(int id, int n) { asm volatile("bar.arrive %0, %1;" ::"r"(id), "r"(n) : "memory"); }
template <int R> __device__ __forceinline__ void reg_dec() { asm volatile("setmaxnreg.dec.sync.aligned.u32 %0;" ::"n"(R)); }
template <int R> __device__ __forceinline__ void reg_inc() { asm volatile("setmaxnreg.inc.sync.aligned.u32 %0;" ::"n"(R)); }

__device__ __forceinline__ void wg_fence() { asm volatile("wgmma.fence.sync.aligned;" ::: "memory"); }
__device__ __forceinline__ void wg_commit() { asm volatile("wgmma.commit_group.sync.aligned;" ::: "memory"); }
template <int N> __device__ __forceinline__ void wg_wait() { asm volatile("wgmma.wait_group.sync.aligned %0;" ::"n"(N) : "memory"); }
template <int N> __device__ __forceinline__ void reg_fence(float (&d)[N]) {
#pragma unroll
  for (int i = 0; i < N; i++) asm volatile("" : "+f"(d[i])::"memory");
}
template <int N> __device__ __forceinline__ void reg_fence_u(uint32_t (&d)[N]) {
#pragma unroll
  for (int i = 0; i < N; i++) asm volatile("" : "+r"(d[i])::"memory");
}
__device__ __forceinline__ uint32_t desc_k(uint32_t addr) { return ((addr & 0x3FFFF) >> 4) | 0x10000u; }
__device__ __forceinline__ uint32_t desc_mn(uint32_t addr, uint32_t lbo) { return ((addr & 0x3FFFF) >> 4) | ((lbo >> 4) << 16); }
__device__ __forceinline__ uint32_t pack_bf16(float lo, float hi) {
  uint32_t r;
  asm("cvt.rn.bf16x2.f32 %0, %1, %2;" : "=r"(r) : "f"(hi), "f"(lo));
  return r;
}
template <typename T> __device__ __forceinline__ T opaque(T v) { asm volatile("" : "+r"(v)); return v; }
__device__ __forceinline__ float bf_lo(uint32_t v) { return __uint_as_float(v << 16); }
__device__ __forceinline__ float bf_hi(uint32_t v) { return __uint_as_float(v & 0xffff0000u); }
__device__ __forceinline__ void stsm_x4(uint32_t addr, uint32_t r0, uint32_t r1, uint32_t r2, uint32_t r3) {
  asm volatile("stmatrix.sync.aligned.m8n8.x4.shared.b16 [%0], {%1, %2, %3, %4};"
               ::"r"(addr), "r"(r0), "r"(r1), "r"(r2), "r"(r3) : "memory");
}
__device__ __forceinline__ float ex2(float x) {
  float y;
  asm("ex2.approx.ftz.f32 %0, %1;" : "=f"(y) : "f"(x));
  return y;
}
struct GeluRow {
  float k1, k3, h;
  __device__ __forceinline__ GeluRow(float r) : k1(0.7978845608028654f * r), k3(0.035677408136300125f * r * r * r), h(0.5f * r) {}
  __device__ __forceinline__ float operator()(float y) const {
    const float u = y * fmaf(y * y, k3, k1);
    float t;
    asm("tanh.approx.f32 %0, %1;" : "=f"(t) : "f"(u));
    const float hy = h * y;
    return fmaf(hy, t, hy);
  }
};
__device__ __forceinline__ float warp_sum(float v) {
#pragma unroll
  for (int o = 16; o; o >>= 1) v += __shfl_xor_sync(0xffffffffu, v, o);
  return v;
}
__device__ __forceinline__ void ln_row16(float (&v)[16], float scale) {
  float s = 0.f;
#pragma unroll
  for (int i = 0; i < 16; i++) s += v[i];
  float mean = warp_sum(s) * (1.f / 512.f);
  float q = 0.f;
#pragma unroll
  for (int i = 0; i < 16; i++) { v[i] -= mean; q = fmaf(v[i], v[i], q); }
  float rstd = scale / sqrtf(warp_sum(q) * (1.f / 512.f) + 1e-5f);
#pragma unroll
  for (int i = 0; i < 16; i++) v[i] *= rstd;
}

__device__ __forceinline__ void flag_add(unsigned int* p, unsigned int v) {
  asm volatile("red.release.gpu.global.add.u32 [%0], %1;" ::"l"(p), "r"(v) : "memory");
}
__device__ __forceinline__ void flag_wait(const unsigned int* p, unsigned int target) {
  asm volatile(
      "{\n.reg .pred p;\n.reg .u32 c, v;\n"
      "mov.u32 c, 0;\n"
      "FLAG_LOOP:\n"
      "ld.acquire.gpu.global.u32 v, [%0];\n"
      "sub.u32 v, v, %1;\n"
      "setp.ge.s32 p, v, 0;\n"
      "@p bra FLAG_DONE;\n"
      "nanosleep.u32 128;\n"
      "add.u32 c, c, 1;\n"
      "setp.lt.u32 p, c, 0x400000;\n"
      "@p bra FLAG_LOOP;\n"
      "trap;\n"
      "FLAG_DONE:\n}"
      ::"l"(p), "r"(target) : "memory");
}
__device__ __forceinline__ void fence_async_all() { asm volatile("fence.proxy.async;" ::: "memory"); }
__device__ __forceinline__ void pdl_launch_dependents() { asm volatile("griddepcontrol.launch_dependents;" ::: "memory"); }
__device__ __forceinline__ void pdl_wait() { asm volatile("griddepcontrol.wait;" ::: "memory"); }

__device__ __forceinline__ void wgmma_ss_n64_tb1(float (&d)[32], uint32_t da, uint32_t db, int scale_d) {
  asm volatile("{\n.reg .pred p;\n.reg .b64 da, db;\nsetp.ne.b32 p, %34, 0;\nmov.b64 da, {%32, 0x40000040};\nmov.b64 db, {%33, 0x40000040};\n"
    "wgmma.mma_async.sync.aligned.m64n64k16.f32.bf16.bf16 {"
    "%0, %1, %2, %3, %4, %5, %6, %7, %8, %9, %10, %11, %12, %13, %14, %15, "
    "%16, %17, %18, %19, %20, %21, %22, %23, %24, %25, %26, %27, %28, %29, %30, %31"
    "}, da, db, p, 1, 1, 0, 1;\n}\n"
    : "+f"(d[0]), "+f"(d[1]), "+f"(d[2]), "+f"(d[3]), "+f"(d[4]), "+f"(d[5]), "+f"(d[6]), "+f"(d[7]),
      "+f"(d[8]), "+f"(d[9]), "+f"(d[10]), "+f"(d[11]), "+f"(d[12]), "+f"(d[13]), "+f"(d[14]), "+f"(d[15]),
      "+f"(d[16]), "+f"(d[17]), "+f"(d[18]), "+f"(d[19]), "+f"(d[20]), "+f"(d[21]), "+f"(d[22]), "+f"(d[23]),
      "+f"(d[24]), "+f"(d[25]), "+f"(d[26]), "+f"(d[27]), "+f"(d[28]), "+f"(d[29]), "+f"(d[30]), "+f"(d[31])
    : "r"(da), "r"(db), "r"(scale_d));
}
__device__ __forceinline__ void wgmma_ss_n128_tb0(float (&d)[64], uint32_t da, uint32_t db, int scale_d) {
  asm volatile("{\n.reg .pred p;\n.reg .b64 da, db;\nsetp.ne.b32 p, %66, 0;\nmov.b64 da, {%64, 0x40000040};\nmov.b64 db, {%65, 0x40000040};\n"
    "wgmma.mma_async.sync.aligned.m64n128k16.f32.bf16.bf16 {"
    "%0, %1, %2, %3, %4, %5, %6, %7, %8, %9, %10, %11, %12, %13, %14, %15, "
    "%16, %17, %18, %19, %20, %21, %22, %23, %24, %25, %26, %27, %28, %29, %30, %31, "
    "%32, %33, %34, %35, %36, %37, %38, %39, %40, %41, %42, %43, %44, %45, %46, %47, "
    "%48, %49, %50, %51, %52, %53, %54, %55, %56, %57, %58, %59, %60, %61, %62, %63"
    "}, da, db, p, 1, 1, 0, 0;\n}\n"
    : "+f"(d[0]), "+f"(d[1]), "+f"(d[2]), "+f"(d[3]), "+f"(d[4]), "+f"(d[5]), "+f"(d[6]), "+f"(d[7]),
      "+f"(d[8]), "+f"(d[9]), "+f"(d[10]), "+f"(d[11]), "+f"(d[12]), "+f"(d[13]), "+f"(d[14]), "+f"(d[15]),
      "+f"(d[16]), "+f"(d[17]), "+f"(d[18]), "+f"(d[19]), "+f"(d[20]), "+f"(d[21]), "+f"(d[22]), "+f"(d[23]),
      "+f"(d[24]), "+f"(d[25]), "+f"(d[26]), "+f"(d[27]), "+f"(d[28]), "+f"(d[29]), "+f"(d[30]), "+f"(d[31]),
      "+f"(d[32]), "+f"(d[33]), "+f"(d[34]), "+f"(d[35]), "+f"(d[36]), "+f"(d[37]), "+f"(d[38]), "+f"(d[39]),
      "+f"(d[40]), "+f"(d[41]), "+f"(d[42]), "+f"(d[43]), "+f"(d[44]), "+f"(d[45]), "+f"(d[46]), "+f"(d[47]),
      "+f"(d[48]), "+f"(d[49]), "+f"(d[50]), "+f"(d[51]), "+f"(d[52]), "+f"(d[53]), "+f"(d[54]), "+f"(d[55]),
      "+f"(d[56]), "+f"(d[57]), "+f"(d[58]), "+f"(d[59]), "+f"(d[60]), "+f"(d[61]), "+f"(d[62]), "+f"(d[63])
    : "r"(da), "r"(db), "r"(scale_d));
}
__device__ __forceinline__ void wgmma_ss_n128_tb1(float (&d)[64], uint32_t da, uint32_t db, int scale_d) {
  asm volatile("{\n.reg .pred p;\n.reg .b64 da, db;\nsetp.ne.b32 p, %66, 0;\nmov.b64 da, {%64, 0x40000040};\nmov.b64 db, {%65, 0x40000040};\n"
    "wgmma.mma_async.sync.aligned.m64n128k16.f32.bf16.bf16 {"
    "%0, %1, %2, %3, %4, %5, %6, %7, %8, %9, %10, %11, %12, %13, %14, %15, "
    "%16, %17, %18, %19, %20, %21, %22, %23, %24, %25, %26, %27, %28, %29, %30, %31, "
    "%32, %33, %34, %35, %36, %37, %38, %39, %40, %41, %42, %43, %44, %45, %46, %47, "
    "%48, %49, %50, %51, %52, %53, %54, %55, %56, %57, %58, %59, %60, %61, %62, %63"
    "}, da, db, p, 1, 1, 0, 1;\n}\n"
    : "+f"(d[0]), "+f"(d[1]), "+f"(d[2]), "+f"(d[3]), "+f"(d[4]), "+f"(d[5]), "+f"(d[6]), "+f"(d[7]),
      "+f"(d[8]), "+f"(d[9]), "+f"(d[10]), "+f"(d[11]), "+f"(d[12]), "+f"(d[13]), "+f"(d[14]), "+f"(d[15]),
      "+f"(d[16]), "+f"(d[17]), "+f"(d[18]), "+f"(d[19]), "+f"(d[20]), "+f"(d[21]), "+f"(d[22]), "+f"(d[23]),
      "+f"(d[24]), "+f"(d[25]), "+f"(d[26]), "+f"(d[27]), "+f"(d[28]), "+f"(d[29]), "+f"(d[30]), "+f"(d[31]),
      "+f"(d[32]), "+f"(d[33]), "+f"(d[34]), "+f"(d[35]), "+f"(d[36]), "+f"(d[37]), "+f"(d[38]), "+f"(d[39]),
      "+f"(d[40]), "+f"(d[41]), "+f"(d[42]), "+f"(d[43]), "+f"(d[44]), "+f"(d[45]), "+f"(d[46]), "+f"(d[47]),
      "+f"(d[48]), "+f"(d[49]), "+f"(d[50]), "+f"(d[51]), "+f"(d[52]), "+f"(d[53]), "+f"(d[54]), "+f"(d[55]),
      "+f"(d[56]), "+f"(d[57]), "+f"(d[58]), "+f"(d[59]), "+f"(d[60]), "+f"(d[61]), "+f"(d[62]), "+f"(d[63])
    : "r"(da), "r"(db), "r"(scale_d));
}
__device__ __forceinline__ void wgmma_ss_n224_tb1(float (&d)[112], uint32_t da, uint32_t db, int scale_d) {
  asm volatile("{\n.reg .pred p;\n.reg .b64 da, db;\nsetp.ne.b32 p, %114, 0;\nmov.b64 da, {%112, 0x40000040};\nmov.b64 db, {%113, 0x40000040};\n"
    "wgmma.mma_async.sync.aligned.m64n224k16.f32.bf16.bf16 {"
    "%0, %1, %2, %3, %4, %5, %6, %7, %8, %9, %10, %11, %12, %13, %14, %15, "
    "%16, %17, %18, %19, %20, %21, %22, %23, %24, %25, %26, %27, %28, %29, %30, %31, "
    "%32, %33, %34, %35, %36, %37, %38, %39, %40, %41, %42, %43, %44, %45, %46, %47, "
    "%48, %49, %50, %51, %52, %53, %54, %55, %56, %57, %58, %59, %60, %61, %62, %63, "
    "%64, %65, %66, %67, %68, %69, %70, %71, %72, %73, %74, %75, %76, %77, %78, %79, "
    "%80, %81, %82, %83, %84, %85, %86, %87, %88, %89, %90, %91, %92, %93, %94, %95, "
    "%96, %97, %98, %99, %100, %101, %102, %103, %104, %105, %106, %107, %108, %109, %110, %111"
    "}, da, db, p, 1, 1, 0, 1;\n}\n"
    : "+f"(d[0]), "+f"(d[1]), "+f"(d[2]), "+f"(d[3]), "+f"(d[4]), "+f"(d[5]), "+f"(d[6]), "+f"(d[7]),
      "+f"(d[8]), "+f"(d[9]), "+f"(d[10]), "+f"(d[11]), "+f"(d[12]), "+f"(d[13]), "+f"(d[14]), "+f"(d[15]),
      "+f"(d[16]), "+f"(d[17]), "+f"(d[18]), "+f"(d[19]), "+f"(d[20]), "+f"(d[21]), "+f"(d[22]), "+f"(d[23]),
      "+f"(d[24]), "+f"(d[25]), "+f"(d[26]), "+f"(d[27]), "+f"(d[28]), "+f"(d[29]), "+f"(d[30]), "+f"(d[31]),
      "+f"(d[32]), "+f"(d[33]), "+f"(d[34]), "+f"(d[35]), "+f"(d[36]), "+f"(d[37]), "+f"(d[38]), "+f"(d[39]),
      "+f"(d[40]), "+f"(d[41]), "+f"(d[42]), "+f"(d[43]), "+f"(d[44]), "+f"(d[45]), "+f"(d[46]), "+f"(d[47]),
      "+f"(d[48]), "+f"(d[49]), "+f"(d[50]), "+f"(d[51]), "+f"(d[52]), "+f"(d[53]), "+f"(d[54]), "+f"(d[55]),
      "+f"(d[56]), "+f"(d[57]), "+f"(d[58]), "+f"(d[59]), "+f"(d[60]), "+f"(d[61]), "+f"(d[62]), "+f"(d[63]),
      "+f"(d[64]), "+f"(d[65]), "+f"(d[66]), "+f"(d[67]), "+f"(d[68]), "+f"(d[69]), "+f"(d[70]), "+f"(d[71]),
      "+f"(d[72]), "+f"(d[73]), "+f"(d[74]), "+f"(d[75]), "+f"(d[76]), "+f"(d[77]), "+f"(d[78]), "+f"(d[79]),
      "+f"(d[80]), "+f"(d[81]), "+f"(d[82]), "+f"(d[83]), "+f"(d[84]), "+f"(d[85]), "+f"(d[86]), "+f"(d[87]),
      "+f"(d[88]), "+f"(d[89]), "+f"(d[90]), "+f"(d[91]), "+f"(d[92]), "+f"(d[93]), "+f"(d[94]), "+f"(d[95]),
      "+f"(d[96]), "+f"(d[97]), "+f"(d[98]), "+f"(d[99]), "+f"(d[100]), "+f"(d[101]), "+f"(d[102]), "+f"(d[103]),
      "+f"(d[104]), "+f"(d[105]), "+f"(d[106]), "+f"(d[107]), "+f"(d[108]), "+f"(d[109]), "+f"(d[110]), "+f"(d[111])
    : "r"(da), "r"(db), "r"(scale_d));
}
__device__ __forceinline__ void wgmma_rs_n128_tb1(float (&d)[64], uint32_t a0, uint32_t a1, uint32_t a2, uint32_t a3, uint32_t db, int scale_d) {
  asm volatile("{\n.reg .pred p;\n.reg .b64 db;\nsetp.ne.b32 p, %69, 0;\nmov.b64 db, {%68, 0x40000040};\n"
    "wgmma.mma_async.sync.aligned.m64n128k16.f32.bf16.bf16 {"
    "%0, %1, %2, %3, %4, %5, %6, %7, %8, %9, %10, %11, %12, %13, %14, %15, "
    "%16, %17, %18, %19, %20, %21, %22, %23, %24, %25, %26, %27, %28, %29, %30, %31, "
    "%32, %33, %34, %35, %36, %37, %38, %39, %40, %41, %42, %43, %44, %45, %46, %47, "
    "%48, %49, %50, %51, %52, %53, %54, %55, %56, %57, %58, %59, %60, %61, %62, %63"
    "}, {%64, %65, %66, %67}, db, p, 1, 1, 1;\n}\n"
    : "+f"(d[0]), "+f"(d[1]), "+f"(d[2]), "+f"(d[3]), "+f"(d[4]), "+f"(d[5]), "+f"(d[6]), "+f"(d[7]),
      "+f"(d[8]), "+f"(d[9]), "+f"(d[10]), "+f"(d[11]), "+f"(d[12]), "+f"(d[13]), "+f"(d[14]), "+f"(d[15]),
      "+f"(d[16]), "+f"(d[17]), "+f"(d[18]), "+f"(d[19]), "+f"(d[20]), "+f"(d[21]), "+f"(d[22]), "+f"(d[23]),
      "+f"(d[24]), "+f"(d[25]), "+f"(d[26]), "+f"(d[27]), "+f"(d[28]), "+f"(d[29]), "+f"(d[30]), "+f"(d[31]),
      "+f"(d[32]), "+f"(d[33]), "+f"(d[34]), "+f"(d[35]), "+f"(d[36]), "+f"(d[37]), "+f"(d[38]), "+f"(d[39]),
      "+f"(d[40]), "+f"(d[41]), "+f"(d[42]), "+f"(d[43]), "+f"(d[44]), "+f"(d[45]), "+f"(d[46]), "+f"(d[47]),
      "+f"(d[48]), "+f"(d[49]), "+f"(d[50]), "+f"(d[51]), "+f"(d[52]), "+f"(d[53]), "+f"(d[54]), "+f"(d[55]),
      "+f"(d[56]), "+f"(d[57]), "+f"(d[58]), "+f"(d[59]), "+f"(d[60]), "+f"(d[61]), "+f"(d[62]), "+f"(d[63])
    : "r"(a0), "r"(a1), "r"(a2), "r"(a3), "r"(db), "r"(scale_d));
}

template <int N>
__device__ __forceinline__ void stsm_block64(uint32_t tile, const float (&acc)[N], int t0, int lane) {
  const int row = (lane & 7) + ((lane >> 3) & 1) * 8;
  const uint32_t rbase = tile + row * 128;
#pragma unroll
  for (int j = 0; j < 4; j++) {
    const int t = t0 + 2 * j;
    const int chunk = 2 * j + (lane >> 4);
    const uint32_t addr = rbase + ((chunk ^ (lane & 7)) << 4);
    stsm_x4(addr, pack_bf16(acc[4 * t + 0], acc[4 * t + 1]), pack_bf16(acc[4 * t + 2], acc[4 * t + 3]),
            pack_bf16(acc[4 * t + 4], acc[4 * t + 5]), pack_bf16(acc[4 * t + 6], acc[4 * t + 7]));
  }
}

#define X_WQT 7
#define X_LNT 0
#define X_NB 4
constexpr int P1_NS = 5;
constexpr int P1_A = 0;
constexpr int P1_RING = 131072;
constexpr int P1_STG = P1_RING + P1_NS * 16384;
constexpr int P1_BAR = P1_STG + 16384;
constexpr int P1_SMEM = P1_BAR + 256;
constexpr float SM_SCALE = 0.08838834764831845f * 1.4426950408889634f;

__global__ void __launch_bounds__(384, 1)
k_p1(const __grid_constant__ CUtensorMap tm_ckv, const __grid_constant__ CUtensorMap tm_wuk,
     const __grid_constant__ CUtensorMap tm_wuv, const __grid_constant__ CUtensorMap tm_kvst,
     const bf16* __restrict__ x, const bf16* __restrict__ wq) {
  extern __shared__ __align__(1024) uint8_t smem[];
  const uint32_t sb = smem_u32(smem);
  const uint32_t bar_a = sb + P1_BAR;
  const uint32_t bar_full = bar_a + 64;
  const uint32_t bar_empty = bar_full + 8 * P1_NS;
  const uint32_t bar_go = bar_empty + 8 * P1_NS;
  const int tid = threadIdx.x, warp = __shfl_sync(0xffffffffu, tid >> 5, 0), lane = tid & 31;
  const int cta = blockIdx.x, rank = cta & 1, q = cta >> 1;
  const int m = 2 * (q & 7) + rank, g = q >> 3;
  TS_DECL;

  pdl_launch_dependents();
  if (tid == 0) {
    TS(0, 0);
    for (int i = 0; i < 8; i++) mbar_init(bar_a + 8 * i, 1);
    for (int i = 0; i < P1_NS; i++) { mbar_init(bar_full + 8 * i, 1); mbar_init(bar_empty + 8 * i, 8); }
    mbar_init(bar_go, 1);
    asm volatile("fence.mbarrier_init.release.cluster;" ::: "memory");
  }
  __syncthreads();
  cluster_sync_all();

  if (warp < 4) {
    reg_dec<56>();
    if (warp == 0) {
      if (lane == 0) {
        const CUtensorMap* tmw = (g < 4) ? &tm_wuk : &tm_wuv;
        const uint64_t pol = policy_evict_first();
        int slot = 0; uint32_t ph = 1;
        for (int t = 0; t < 8; t++) {
          const int head = (8 * g + t) & 31;
          for (int kb = 0; kb < 8; kb++) {
            if (t == 0) {
              mbar_expect_tx(bar_a + 8 * kb, 16384);
              tma_load_2d_ef(sb + P1_A + kb * 16384, &tm_ckv, kb * 64, m * 128, bar_a + 8 * kb, pol);
            }
            mbar_wait(bar_empty + 8 * slot, ph);
            mbar_expect_tx(bar_full + 8 * slot, 16384);
            tma_load_2d_mc_ef(sb + P1_RING + slot * 16384 + rank * 8192, tmw, head * 128 + rank * 64, kb * 64,
                              bar_full + 8 * slot, (uint16_t)3, pol);
            if (++slot == P1_NS) { slot = 0; ph ^= 1; }
            if (kb == 4) {
              if (t == 0) {
                if ((q & 7) < 3) tma_prefetch_2d(tmw, ((8 * g) & 31) * 128 + rank * 64, (5 + (q & 7)) * 64);
                tma_prefetch_2d(tmw, ((8 * g + 1) & 31) * 128 + rank * 64, (q & 7) * 64);
              }
              if (t < 6) tma_prefetch_2d(tmw, ((8 * g + t + 2) & 31) * 128 + rank * 64, (q & 7) * 64);
              if (t == X_LNT) mbar_arrive(bar_go);
              if (t == X_WQT) {
#pragma unroll 1
                for (int i = 0; i < 4; i++) bulk_prefetch(wq + cta * 16384 + i * 4096, 8192);
              }
            }
          }
        }
      }
    } else {
      if (cta == 0 && warp == 1) g_cnth[lane] = 0;
      mbar_wait(bar_go, 0);
      for (int rr = warp - 1; rr < 16; rr += 3) {
        const int row = cta * 16 + rr;
        const uint4* src = reinterpret_cast<const uint4*>(x + (size_t)row * DM);
        const uint4 u0 = __ldg(src + lane), u1 = __ldg(src + 32 + lane);
        float v[16];
        const uint32_t w[8] = {u0.x, u0.y, u0.z, u0.w, u1.x, u1.y, u1.z, u1.w};
#pragma unroll
        for (int i = 0; i < 8; i++) { v[2 * i] = bf_lo(w[i]); v[2 * i + 1] = bf_hi(w[i]); }
        uint4* hd = reinterpret_cast<uint4*>(g_hp + (size_t)row * DM);
#pragma unroll
        for (int b = 0; b < NBUF; b++) {
          hd[(size_t)b * (SEQ * DM / 8) + lane] = make_uint4(0, 0, 0, 0);
          hd[(size_t)b * (SEQ * DM / 8) + 32 + lane] = make_uint4(0, 0, 0, 0);
        }
        ln_row16(v, SM_SCALE);
        uint4* dst = reinterpret_cast<uint4*>(g_xn + (size_t)row * DM);
        dst[lane] = make_uint4(pack_bf16(v[0], v[1]), pack_bf16(v[2], v[3]), pack_bf16(v[4], v[5]), pack_bf16(v[6], v[7]));
        dst[32 + lane] = make_uint4(pack_bf16(v[8], v[9]), pack_bf16(v[10], v[11]), pack_bf16(v[12], v[13]), pack_bf16(v[14], v[15]));
      }
    }
    if (tid == 0) TS_OUT(0);
    __syncwarp();
    cluster_sync_all();
  } else {
    reg_inc<224>();
    const int wg = (warp >> 2) - 1, ww = warp & 3;
    float acc0[64], acc1[64];
    const uint32_t stg = sb + P1_STG + (warp - 4) * 2048;
    if (wg == 1) named_arrive(4, 256);
    for (int tt = 0; tt < 4; tt++) {
      const int t = 2 * tt + wg;
      int pos = 8 * t;
      int slot = pos % P1_NS; uint32_t ph = (pos / P1_NS) & 1;
      int prev_slot = 0;
      named_sync(4 + wg, 256);
      for (int kb = 0; kb < 8; kb++) {
        if (tt == 0) mbar_wait(bar_a + 8 * kb, 0);
        mbar_wait(bar_full + 8 * slot, ph);
        const uint32_t a0 = desc_k(sb + P1_A) + kb * 1024;
        const uint32_t b0 = desc_mn(sb + P1_RING, 8192) + slot * 1024;
        wg_fence();
#pragma unroll
        for (int ks = 0; ks < 4; ks++) {
          wgmma_ss_n128_tb1(acc0, a0 + ks * 2, b0 + ks * 128, (kb | ks) != 0);
          wgmma_ss_n128_tb1(acc1, a0 + 512 + ks * 2, b0 + ks * 128, (kb | ks) != 0);
        }
        wg_commit();
        if (kb > 0) {
          wg_wait<1>();
          if (lane < 2) mbar_arrive_remote(bar_empty + 8 * prev_slot, lane);
        }
        prev_slot = slot;
        if (++slot == P1_NS) { slot = 0; ph ^= 1; }
      }
      named_arrive(4 + (wg ^ 1), 256);
      wg_wait<0>();
      if (lane < 2) mbar_arrive_remote(bar_empty + 8 * prev_slot, lane);
      reg_fence(acc0); reg_fence(acc1);
      if (tid == 128) { if (tt == 0) TS(0, 3); if (tt == 1) TS(0, 4); if (tt == 2) TS(0, 5); if (tt == 3) TS(0, 6); }
      {
        float n0 = 0.f, n1 = 0.f, n2 = 0.f, n3 = 0.f;
#pragma unroll
        for (int i = 0; i < 16; i++) {
          n0 = fmaf(acc0[4 * i], acc0[4 * i], fmaf(acc0[4 * i + 1], acc0[4 * i + 1], n0));
          n1 = fmaf(acc0[4 * i + 2], acc0[4 * i + 2], fmaf(acc0[4 * i + 3], acc0[4 * i + 3], n1));
          n2 = fmaf(acc1[4 * i], acc1[4 * i], fmaf(acc1[4 * i + 1], acc1[4 * i + 1], n2));
          n3 = fmaf(acc1[4 * i + 2], acc1[4 * i + 2], fmaf(acc1[4 * i + 3], acc1[4 * i + 3], n3));
        }
#pragma unroll
        for (int o = 1; o < 4; o <<= 1) {
          n0 += __shfl_xor_sync(0xffffffffu, n0, o); n1 += __shfl_xor_sync(0xffffffffu, n1, o);
          n2 += __shfl_xor_sync(0xffffffffu, n2, o); n3 += __shfl_xor_sync(0xffffffffu, n3, o);
        }
        unsigned int a = max(__float_as_uint(n0), __float_as_uint(n1)), b = max(__float_as_uint(n2), __float_as_uint(n3));
        a = __reduce_max_sync(0xffffffffu, a);
        b = __reduce_max_sync(0xffffffffu, b);
        if (lane == 0) {
          g_nrm[(8 * g + t) * 128 + m * 8 + ww] = __uint_as_float(a);
          g_nrm[(8 * g + t) * 128 + m * 8 + 4 + ww] = __uint_as_float(b);
        }
      }
      const int grow = (8 * g + t) * SEQ + m * 128 + ww * 16;
      const bool last = tt == 3 && wg == 1;
      if (last) named_sync(6, 256);
#pragma unroll
      for (int b = 0; b < 4; b++) {
        const uint32_t buf = (last && (b & 1)) ? stg - 8192 : stg;
        if (lane == 0) { if (last && b > 0) bulk_wait_read<1>(); else bulk_wait_read<0>(); }
        __syncwarp();
        if (b < 2) stsm_block64(buf, acc0, (b & 1) * 8, lane); else stsm_block64(buf, acc1, (b & 1) * 8, lane);
        fence_async_smem();
        __syncwarp();
        if (lane == 0) { tma_store_2d(&tm_kvst, buf, (b & 1) * 64, grow + (b >> 1) * 64); bulk_commit(); }
      }
      if (tt == 3 && wg == 0) {
        if (lane == 0) bulk_wait_read<0>();
        __syncwarp();
        named_arrive(6, 256);
      }
    }
    if (lane == 0) bulk_wait<0>();
    __syncwarp();
    if (tid == 128) { TS(0, 1); TS_OUT(0); }
    cluster_sync_all();
  }
}

constexpr int P2_NS = 5;
constexpr int P2_QA = 0;
constexpr int P2_QB = 32768;
constexpr int P2_RING = 65536;
constexpr int P2_BAR = P2_RING + P2_NS * 32768;
constexpr int P2_SMEM = P2_BAR + 256;
constexpr float SM_BOUND = 80.f;
constexpr float V_BOUND2 = 1.0e18f;

struct Ring {
  int slot; uint32_t ph;
  __device__ __forceinline__ void next() { if (++slot == P2_NS) { slot = 0; ph ^= 1; } }
};

__device__ __forceinline__ void issue_qk(float (&s)[64], uint32_t qa, uint32_t kb) {
#pragma unroll
  for (int ks = 0; ks < 8; ks++)
    wgmma_ss_n128_tb0(s, qa + (ks >> 2) * 1024 + (ks & 3) * 2, kb + (ks >> 2) * 1024 + (ks & 3) * 2, ks != 0);
}
__device__ __forceinline__ void issue_pv(float (&o)[64], const uint32_t (&p)[32], uint32_t vb) {
#pragma unroll
  for (int ks = 0; ks < 8; ks++)
    wgmma_rs_n128_tb1(o, p[4 * ks], p[4 * ks + 1], p[4 * ks + 2], p[4 * ks + 3], vb + ks * 128, 1);
}

__device__ __forceinline__ float vmax(float a, float b) {
  float r;
  asm volatile("max.f32 %0, %1, %2;" : "=f"(r) : "f"(a), "f"(b));
  return r;
}
__device__ __forceinline__ void sm_shift(float (&s)[64], float (&mx)[2], float (&corr)[2]) {
  float a0 = vmax(s[0], s[8]), b0 = vmax(s[2], s[10]), a1 = vmax(s[1], s[9]), b1 = vmax(s[3], s[11]);
  float a2 = vmax(s[4], s[12]), b2 = vmax(s[6], s[14]), a3 = vmax(s[5], s[13]), b3 = vmax(s[7], s[15]);
#pragma unroll
  for (int j = 4; j < 16; j += 2) {
    a0 = vmax(a0, s[4 * j]);     b0 = vmax(b0, s[4 * j + 2]);
    a1 = vmax(a1, s[4 * j + 1]); b1 = vmax(b1, s[4 * j + 3]);
    a2 = vmax(a2, s[4 * j + 4]); b2 = vmax(b2, s[4 * j + 6]);
    a3 = vmax(a3, s[4 * j + 5]); b3 = vmax(b3, s[4 * j + 7]);
  }
  a0 = vmax(a0, a1); b0 = vmax(b0, b1); a2 = vmax(a2, a3); b2 = vmax(b2, b3);
  float m0 = fmaxf(a0, a2), m1 = fmaxf(b0, b2);
  m0 = fmaxf(m0, __shfl_xor_sync(0xffffffffu, m0, 1));
  m1 = fmaxf(m1, __shfl_xor_sync(0xffffffffu, m1, 1));
  m0 = fmaxf(m0, __shfl_xor_sync(0xffffffffu, m0, 2));
  m1 = fmaxf(m1, __shfl_xor_sync(0xffffffffu, m1, 2));
  m0 = fmaxf(m0, mx[0]); m1 = fmaxf(m1, mx[1]);
  corr[0] = ex2(mx[0] - m0);
  corr[1] = ex2(mx[1] - m1);
  mx[0] = m0; mx[1] = m1;
#pragma unroll
  for (int j = 0; j < 16; j++) { s[4 * j] -= m0; s[4 * j + 1] -= m0; s[4 * j + 2] -= m1; s[4 * j + 3] -= m1; }
}
__device__ __forceinline__ void sm_exp(float (&s)[64], float& s0, float& s1) {
  float sum[4] = {0.f, 0.f, 0.f, 0.f};
#pragma unroll
  for (int j = 0; j < 16; j++) {
    s[4 * j + 0] = ex2(s[4 * j + 0]); s[4 * j + 1] = ex2(s[4 * j + 1]);
    s[4 * j + 2] = ex2(s[4 * j + 2]); s[4 * j + 3] = ex2(s[4 * j + 3]);
    sum[0] += s[4 * j + 0]; sum[1] += s[4 * j + 1]; sum[2] += s[4 * j + 2]; sum[3] += s[4 * j + 3];
  }
  s0 = sum[0] + sum[1]; s1 = sum[2] + sum[3];
}
__device__ __forceinline__ bool named_and(int id, int n, bool v) {
  uint32_t r;
  asm volatile("{\n.reg .pred q, t;\nsetp.ne.u32 q, %1, 0;\nbarrier.cta.red.and.aligned.pred t, %2, %3, q;\nselp.u32 %0, 1, 0, t;\n}"
               : "=r"(r) : "r"((uint32_t)v), "r"(id), "r"(n) : "memory");
  return r != 0;
}
template <int V> struct IntTag { static constexpr int value = V; };
template <int I0, int I1> __device__ __forceinline__ void reg_fence_range(float (&d)[64]) {
#pragma unroll
  for (int i = I0; i < I1; i++) asm volatile("" : "+f"(d[i])::"memory");
}
__device__ __forceinline__ uint32_t mbar_test(uint32_t bar, uint32_t parity) {
  uint32_t d;
  asm volatile("{\n.reg .pred p;\nmbarrier.test_wait.parity.shared::cta.b64 p, [%1], %2;\nselp.u32 %0, 1, 0, p;\n}"
               : "=r"(d) : "r"(bar), "r"(parity) : "memory");
  return d;
}

__device__ __forceinline__ void to_p(uint32_t (&p)[32], const float (&s)[64]) {
#pragma unroll
  for (int i = 0; i < 32; i++) p[i] = pack_bf16(s[2 * i], s[2 * i + 1]);
}

__global__ void __launch_bounds__(384, 1)
k_p2(const __grid_constant__ CUtensorMap tm_xn0, const __grid_constant__ CUtensorMap tm_xn1, const __grid_constant__ CUtensorMap tm_wq,
     const __grid_constant__ CUtensorMap tm_kv, const __grid_constant__ CUtensorMap tm_wo,
     const __grid_constant__ CUtensorMap tm_h, const bf16* __restrict__ x, const bf16* __restrict__ w1, const bf16* __restrict__ w2,
     const bf16* __restrict__ w3, const bf16* __restrict__ w4) {
  extern __shared__ __align__(1024) uint8_t smem[];
  const uint32_t sb = smem_u32(smem);
  const uint32_t bar_full = sb + P2_BAR;
  const uint32_t bar_empty = bar_full + 8 * P2_NS;
  const uint32_t bar_staged = bar_empty + 8 * P2_NS;
  const uint32_t bar_sfree = bar_staged + 32;
  const uint32_t bar_xq = bar_sfree + 32;
  const uint32_t bar_q0 = bar_xq + 32;
  const uint32_t bar_drain = bar_xq + 16;
  const int tid = threadIdx.x, warp = __shfl_sync(0xffffffffu, tid >> 5, 0), lane = tid & 31;
  const int cta = blockIdx.x, rank = cta & 1, hp = cta >> 3, jj = (cta >> 1) & 3;
  TS_DECL;

  pdl_launch_dependents();
  if (tid == 0) {
    TS(1, 0);
    for (int i = 0; i < P2_NS; i++) { mbar_init(bar_full + 8 * i, 1); mbar_init(bar_empty + 8 * i, 16); }
    asm volatile("fence.mbarrier_init.release.cluster;" ::: "memory");
  }
  if (tid == 32) {
    for (int i = 0; i < 4; i++) { mbar_init(bar_staged + 8 * i, 4); mbar_init(bar_sfree + 8 * i, 1); }
    for (int i = 0; i < 2; i++) { mbar_init(bar_xq + 8 * i, 1); mbar_init(bar_drain + 8 * i, 2); }
    mbar_init(bar_q0, 1);
    asm volatile("fence.mbarrier_init.release.cluster;" ::: "memory");
  }
  if (tid == 64) { prefetch_tmap(rank ? &tm_xn1 : &tm_xn0); prefetch_tmap(&tm_wq); prefetch_tmap(&tm_kv); prefetch_tmap(&tm_wo); prefetch_tmap(&tm_h); }
  __syncthreads();
  cluster_sync_all();
  if (warp < 4) {
    reg_dec<40>();
    const CUtensorMap* tm_xn = rank ? &tm_xn1 : &tm_xn0;
    if (tid == 0) {
      pdl_wait();
#pragma unroll 1
      for (int c = 0; c < 3; c++) {
        const uint32_t fb = c < 2 ? bar_xq + 8 * c : bar_full + 32;
        mbar_expect_tx(fb, 32768);
        tma_load_4d(c < 2 ? sb + P2_QA + c * 32768 : sb + P2_RING + 4 * 32768, tm_xn, 0, 0, (7 - jj) * 4 + rank, 2 * c, fb);
        if (c < 2) {
#pragma unroll 1
          for (int slot = 2 * c; slot < 2 * c + 2; slot++) {
            mbar_expect_tx(bar_full + 8 * slot, 32768);
            tma_load_3d_mc(sb + P2_RING + slot * 32768 + rank * 16384, &tm_wq, 0, slot * 64, hp * 4 + 2 * rank, bar_full + 8 * slot, (uint16_t)3);
          }
        }
      }
    }
  if (warp != 0) pdl_wait();
    if (warp == 0) {
      if (lane == 0) {
        Ring r{0, 0};
        auto acquire = [&]() -> uint32_t {
          mbar_wait(bar_empty + 8 * r.slot, r.ph);
          mbar_expect_tx(bar_full + 8 * r.slot, 32768);
          return sb + P2_RING + r.slot * 32768;
        };
        auto load_tile = [&](const CUtensorMap* tm, int c0, int c1) {
          const uint32_t d = acquire();
          tma_load_2d_mc(d + rank * 16384, tm, c0 + rank * 64, c1, bar_full + 8 * r.slot, (uint16_t)3);
          r.next();
        };
#pragma unroll 1
        for (int item = 0; item < 2; item++) {
          const int J = item == 0 ? 7 - jj : jj;
          const int n = 2 * J + 2;
#pragma unroll 1
          for (int c = (item == 0 ? 2 : 0); c < 4; c++) {
            if (item > 0 && c >= 2) {
              const int i = c - 2;
              mbar_wait(bar_drain + 8 * i, 0);
              mbar_expect_tx(bar_xq + 8 * i, 32768);
              tma_load_4d(sb + (i == 0 ? P2_QB : P2_QA), tm_xn, 0, 0, J * 4 + rank, 2 * c, bar_xq + 8 * i);
            }
            if (item == 0 ? c == 3 : c < 2) {
              const uint32_t d = acquire();
              tma_load_4d(d, tm_xn, 0, 0, J * 4 + rank, 2 * c, bar_full + 8 * r.slot);
              r.next();
            }
#pragma unroll 1
            for (int hf = 0; hf < 2; hf++) {
              const uint32_t d = acquire();
              tma_load_3d_mc(d + rank * 16384, &tm_wq, 0, c * 128 + hf * 64, hp * 4 + 2 * rank, bar_full + 8 * r.slot, (uint16_t)3);
              r.next();
            }
          }
#pragma unroll 1
          for (int s2 = 0; s2 < 4 * n + 8; s2++) {
            if (s2 < 4 * n) {
              const int hh = s2 >= 2 * n, t = s2 - hh * 2 * n;
              const int j = (t + 1) >> 1;
              const bool isv = (t > 0 && !(t & 1)) || t == 2 * n - 1;
              const int tile = isv ? (t == 2 * n - 1 ? 0 : n - j) : n - 1 - j;
              load_tile(&tm_kv, 0, ((isv ? NH : 0) + 2 * hp + hh) * SEQ + tile * 128);
            } else {
              const int c = s2 - 4 * n;
              load_tile(&tm_wo, (c >> 1) * 128, (2 * hp + (c & 1)) * 128);
            }
          }
        }
      }
    } else if (warp < 3) {
      const int w = warp - 1;
      CY2_DECL;
#pragma unroll 1
      for (int item = 0; item < 2; item++) {
        const int J = item == 0 ? 7 - jj : jj;
        const int grow = (hp % NBUF) * SEQ + J * 256 + (w == 0 ? rank * 64 : 192 - rank * 64) + (lane & 3) * 16;
        const int blk = (lane >> 2) & 1;
#pragma unroll 1
        for (int c = 0; c < 4; c++) {
          const int set = c & 1, use = item * 2 + (c >> 1);
          CY2(0, mbar_wait(bar_staged + 8 * (2 * w + set), use & 1));
          CY2(1, fence_async_smem());
          if (lane < 8) {
            const uint32_t src = sb + (set == 0 ? P2_QB : P2_QA) + blk * 16384 + w * 8192 + (lane & 3) * 2048;
            tma_red_add_2d(&tm_h, src, c * 128 + blk * 64, grow);
            bulk_commit();
            CY2(2, bulk_wait_read<0>());
          }
          __syncwarp();
          if (lane == 0) {
            mbar_arrive(bar_sfree + 8 * (2 * w + set));
            if (item == 0 && c >= 2) mbar_arrive(bar_drain + 8 * set);
          }
        }
        bulk_wait<0>();
        fence_async_all();
        __syncwarp();
        if (lane == 0) flag_add(&g_cnth[J * 4 + (w == 0 ? rank : 3 - rank)], 1);
      }
      CY2(3, bulk_wait<0>());
      CY2_OUT(warp);
    } else {
      mbar_wait(bar_q0, 0);
      if (lane < 2) tma_prefetch_2d(&tm_wo, (cta & 7) * 64, (2 * hp + lane) * 128);
      const uint32_t* wp = reinterpret_cast<const uint32_t*>(w3 + cta * 14);
      float cs[14];
#pragma unroll
      for (int i = 0; i < 14; i++) cs[i] = 0.f;
#pragma unroll 1
      for (int k = lane; k < DM; k += 32) {
#pragma unroll
        for (int i = 0; i < 7; i++) {
          const uint32_t u = __ldg(wp + (size_t)k * (FF / 2) + i);
          cs[2 * i] += bf_lo(u); cs[2 * i + 1] += bf_hi(u);
        }
      }
#pragma unroll
      for (int i = 0; i < 14; i++) {
        const float t = warp_sum(cs[i]);
        if (lane == 0) g_cs3[cta * 14 + i] = t;
      }
      mbar_wait(bar_staged, 0);
      if (lane == 0) {
        bulk_prefetch(x + cta * 8192, 16384);
        bulk_prefetch(w1 + cta * 2048, 4096);
        bulk_prefetch(w2 + cta * 2048, 4096);
        bulk_prefetch(w3 + cta * 7168, 14336);
        bulk_prefetch(w4 + cta * 7168, 14336);
      }
    }
    if (tid == 0) TS_OUT(1);
    __syncwarp();
    cluster_sync_all();
  } else {
    reg_inc<232>();
    pdl_wait();
    const int wg = (warp >> 2) - 1, ww = warp & 3;
    const uint32_t kdesc0 = desc_k(sb + P2_RING), vdesc0 = desc_mn(sb + P2_RING, 16384), wdesc0 = desc_mn(sb + P2_RING, 8192);
    const uint32_t qa_w = sb + P2_QA + wg * 8192, qb_w = sb + P2_QB + wg * 8192;
    Ring r{0, 0};
    auto release = [&](int slot) { if (lane < 2) mbar_arrive_remote(bar_empty + 8 * slot, lane); };
    auto wait_full = [&]() { mbar_wait(bar_full + 8 * r.slot, r.ph); };
    if (wg == 1) named_arrive(4, 256);
    CYC_DECL;
    CY2_DECL;
    float4 nrm[4];
#pragma unroll
    for (int i = 0; i < 4; i++)
      asm volatile("ld.global.cg.v4.f32 {%0, %1, %2, %3}, [%4];" : "=f"(nrm[i].x), "=f"(nrm[i].y), "=f"(nrm[i].z), "=f"(nrm[i].w)
                   : "l"(g_nrm + ((i >> 1) * NH + 2 * hp + (i & 1)) * 128 + lane * 4));
    float k2a = 0.f, k2b = 0.f;

    for (int item = 0; item < 2; item++) {
      const int J = item == 0 ? 7 - jj : jj;
      const int n = 2 * J + 2;
      if (tid == 128) { if (item == 0) TS(1, 2); else TSX(1, 6); }
      bool fast0, fast1;
      {
        float qa[64], qb[64];
#pragma unroll
        for (int i = 0; i < 64; i++) { qa[i] = 0.f; qb[i] = 0.f; }
        for (int c = 0; c < 4; c++) {
          const bool in_q = item == 0 ? c < 2 : c >= 2;
          int aslot = 0;
          uint32_t a0;
          if (in_q) {
            mbar_wait(bar_xq + 8 * (c & 1), item);
            a0 = desc_k(sb + P2_QA) + ((c & 1) ^ item) * 2048 + wg * 512;
          } else {
            CY2(0, wait_full());
            aslot = r.slot;
            a0 = kdesc0 + aslot * 2048 + wg * 512;
            r.next();
          }
#pragma unroll
          for (int hf = 0; hf < 2; hf++) {
            CY2(0, wait_full());
            const uint32_t b0 = wdesc0 + r.slot * 2048;
            wg_fence();
#pragma unroll
            for (int ks = 0; ks < 4; ks++) {
              wgmma_ss_n128_tb1(qa, a0 + hf * 1024 + ks * 2, b0 + ks * 128, 1);
              wgmma_ss_n128_tb1(qb, a0 + hf * 1024 + ks * 2, b0 + 1024 + ks * 128, 1);
            }
            wg_commit();
            CY2(1, wg_wait<0>());
            release(r.slot);
            if (hf == 1 && !in_q) release(aslot);
            r.next();
          }
        }
        reg_fence(qa); reg_fence(qb);
        float na0 = 0.f, na1 = 0.f, nb0 = 0.f, nb1 = 0.f;
#pragma unroll
        for (int i = 0; i < 16; i++) {
          na0 = fmaf(qa[4 * i], qa[4 * i], fmaf(qa[4 * i + 1], qa[4 * i + 1], na0));
          na1 = fmaf(qa[4 * i + 2], qa[4 * i + 2], fmaf(qa[4 * i + 3], qa[4 * i + 3], na1));
          nb0 = fmaf(qb[4 * i], qb[4 * i], fmaf(qb[4 * i + 1], qb[4 * i + 1], nb0));
          nb1 = fmaf(qb[4 * i + 2], qb[4 * i + 2], fmaf(qb[4 * i + 3], qb[4 * i + 3], nb1));
        }
#pragma unroll
        for (int o = 1; o < 4; o <<= 1) {
          na0 += __shfl_xor_sync(0xffffffffu, na0, o); na1 += __shfl_xor_sync(0xffffffffu, na1, o);
          nb0 += __shfl_xor_sync(0xffffffffu, nb0, o); nb1 += __shfl_xor_sync(0xffffffffu, nb1, o);
        }
        if (item == 0) {
          float v[4];
#pragma unroll
          for (int i = 0; i < 4; i++)
            v[i] = __uint_as_float(__reduce_max_sync(0xffffffffu, max(max(__float_as_uint(nrm[i].x), __float_as_uint(nrm[i].y)),
                                                                     max(__float_as_uint(nrm[i].z), __float_as_uint(nrm[i].w)))));
          k2a = (v[2] <= V_BOUND2) ? v[0] * 1.02f : INFINITY;
          k2b = (v[3] <= V_BOUND2) ? v[1] * 1.02f : INFINITY;
        }
        const float lim = SM_BOUND * SM_BOUND;
        const bool oka = (na0 * k2a <= lim) && (na1 * k2a <= lim), okb = (nb0 * k2b <= lim) && (nb1 * k2b <= lim);
        const int ln = opaque(lane);
        const uint32_t wa = qa_w + ww * 2048, wb = qb_w + ww * 2048;
        stsm_block64(wa, qa, 0, ln);
        stsm_block64(wa + 16384, qa, 8, ln);
        stsm_block64(wb, qb, 0, ln);
        stsm_block64(wb + 16384, qb, 8, ln);
        fence_async_smem();
        if (item == 0 && tid == 128) mbar_arrive(bar_q0);
        fast0 = __all_sync(0xffffffffu, named_and(2 + wg, 128, oka));
        fast1 = __all_sync(0xffffffffu, named_and(2 + wg, 128, okb));
      }
      if (tid == 128) { if (item == 0) TS(1, 3); else TSX(1, 7); }
      uint32_t p[32];
#pragma unroll 1
      for (int hh = 0; hh < 2; hh++) {
        const uint32_t qd = desc_k(hh == 0 ? qa_w : qb_w);
        float o[64], l[2];
        const bool safe = !(hh == 0 ? fast0 : fast1);
        {
          float mx[2] = {-INFINITY, -INFINITY}, corr[2] = {1.f, 1.f};
          if (wg == 0) {
            named_sync(4, 256);
            named_arrive(5, 256);
            wait_full(); release(r.slot); r.next();
          }
          {
            float s[64];
            wait_full();
            named_sync(4 + wg, 256);
            wg_fence();
            issue_qk(s, qd, kdesc0 + r.slot * 2048);
            wg_commit();
            named_arrive(4 + (wg ^ 1), 256);
            wg_wait<0>();
            release(r.slot);
            r.next();
            reg_fence(s);
            {
              const int ln = opaque(lane);
              const int dg = ((wg ^ rank) == 0 ? 0 : 8) + 2 * ww;
              const int d0 = (ln >> 2) - (ln & 3) * 2;
              auto mask = [&](auto tag) {
                constexpr int T = decltype(tag)::value;
#pragma unroll
                for (int j = T; j < 16; j++) {
                  const int c = 8 * (j - T);
                  if (j >= T + 2) { s[4 * j] = -INFINITY; s[4 * j + 1] = -INFINITY; s[4 * j + 2] = -INFINITY; s[4 * j + 3] = -INFINITY; }
                  else {
                    if (c > d0) s[4 * j] = -INFINITY;
                    if (c + 1 > d0) s[4 * j + 1] = -INFINITY;
                    if (c > d0 + 8) s[4 * j + 2] = -INFINITY;
                    if (c + 1 > d0 + 8) s[4 * j + 3] = -INFINITY;
                  }
                }
              };
              switch (dg) {
                case 0: mask(IntTag<0>{}); break;
                case 2: mask(IntTag<2>{}); break;
                case 4: mask(IntTag<4>{}); break;
                case 6: mask(IntTag<6>{}); break;
                case 8: mask(IntTag<8>{}); break;
                case 10: mask(IntTag<10>{}); break;
                case 12: mask(IntTag<12>{}); break;
                default: mask(IntTag<14>{}); break;
              }
            }
            if (__builtin_expect(safe, 0)) sm_shift(s, mx, corr);
            sm_exp(s, l[0], l[1]);
            to_p(p, s);
          }
          if (wg == 0) { wait_full(); release(r.slot); r.next(); }
#pragma unroll
          for (int i = 0; i < 64; i++) o[i] = 0.f;
          corr[0] = 1.f; corr[1] = 1.f;
          uint32_t okk = 0, okv = 0;
          auto rescale = [&]() {
#pragma unroll
            for (int i = 0; i < 16; i++) {
              o[4 * i] *= corr[0]; o[4 * i + 1] *= corr[0]; o[4 * i + 2] *= corr[1]; o[4 * i + 3] *= corr[1];
            }
          };
#pragma unroll 1
          for (int cnt = n - 1 - (wg ^ 1); cnt > 0; cnt--) {
            float s[64];
            const int ks = r.slot;
            CYC_START;
            if (!okk) wait_full();
            r.next();
            CYC(0);
            named_sync(4 + wg, 256);
            CYC(1);
            wg_fence();
            issue_qk(s, qd, kdesc0 + ks * 2048);
            wg_commit();
            CYC(2);
            const int vs = r.slot;
            if (!okv) wait_full();
            r.next();
            if (__builtin_expect(safe, 0)) rescale();
            CYC(3);
            wg_fence();
            issue_pv(o, p, vdesc0 + vs * 2048);
            wg_commit();
            named_arrive(4 + (wg ^ 1), 256);
            {
              Ring r2 = r;
              okk = mbar_test(bar_full + 8 * r2.slot, r2.ph);
              r2.next();
              okv = mbar_test(bar_full + 8 * r2.slot, r2.ph);
            }
            CYC(4);
            wg_wait<1>();
            CYC(5);
            release(ks);
            reg_fence(s);
            float s0, s1;
            if (__builtin_expect(safe, 0)) sm_shift(s, mx, corr);
            sm_exp(s, s0, s1);
            if (__any_sync(0xffffffffu, s0 + s1 > 1e37f)) mbar_wait(bar_full + 8 * vs, 0);
            CYC(6);
            wg_wait<0>();
            CYC(7);
            release(vs);
            reg_fence(o); reg_fence_u(p);
            l[0] = fmaf(l[0], corr[0], s0); l[1] = fmaf(l[1], corr[1], s1);
            to_p(p, s);
            CYC(8);
            CYC_N();
          }
          if (__builtin_expect(safe, 0)) rescale();
          if (!okk) wait_full();
          wg_fence();
          issue_pv(o, p, vdesc0 + r.slot * 2048);
          wg_commit();
          wg_wait<0>();
          release(r.slot);
          r.next();
          reg_fence(o); reg_fence_u(p);
        }
        float l0 = l[0], l1 = l[1];
        l0 += __shfl_xor_sync(0xffffffffu, l0, 1); l1 += __shfl_xor_sync(0xffffffffu, l1, 1);
        l0 += __shfl_xor_sync(0xffffffffu, l0, 2); l1 += __shfl_xor_sync(0xffffffffu, l1, 2);
        const float i0 = __fdividef(1.f, l0), i1 = __fdividef(1.f, l1);
#pragma unroll
        for (int i = 0; i < 16; i++) {
          o[4 * i] *= i0; o[4 * i + 1] *= i0; o[4 * i + 2] *= i1; o[4 * i + 3] *= i1;
        }
        if (hh == 0) {
          const int ln = opaque(lane);
          const uint32_t wa = qa_w + ww * 2048;
          stsm_block64(wa, o, 0, ln);
          stsm_block64(wa + 16384, o, 8, ln);
        } else {
          to_p(p, o);
        }
      }
      if (tid == 128) { if (item == 0) TS(1, 4); else TSX(1, 8); }
      {
        uint32_t pa[32];
        {
          const int ln = opaque(lane);
          const int row = (ln & 7) + ((ln >> 3) & 1) * 8;
          const uint32_t rb = qa_w + ww * 2048 + row * 128;
          __syncwarp();
#pragma unroll
          for (int ks = 0; ks < 8; ks++) {
            const uint32_t ad = rb + (ks >> 2) * 16384 + (((2 * (ks & 3) + (ln >> 4)) ^ (ln & 7)) << 4);
            asm volatile("ldmatrix.sync.aligned.m8n8.x4.shared.b16 {%0, %1, %2, %3}, [%4];"
                         : "=r"(pa[4 * ks]), "=r"(pa[4 * ks + 1]), "=r"(pa[4 * ks + 2]), "=r"(pa[4 * ks + 3]) : "r"(ad) : "memory");
          }
        }
#pragma unroll 1
        for (int c = 0; c < 4; c++) {
          float acc[64];
          CY2(3, wait_full());
          const int sa = r.slot;
          r.next();
          wg_fence();
#pragma unroll
          for (int ks = 0; ks < 8; ks++)
            wgmma_rs_n128_tb1(acc, pa[4 * ks], pa[4 * ks + 1], pa[4 * ks + 2], pa[4 * ks + 3], vdesc0 + sa * 2048 + ks * 128, ks != 0);
          wg_commit();
          CY2(3, wait_full());
          const int sb2 = r.slot;
          r.next();
          wg_fence();
#pragma unroll
          for (int ks = 0; ks < 8; ks++)
            wgmma_rs_n128_tb1(acc, p[4 * ks], p[4 * ks + 1], p[4 * ks + 2], p[4 * ks + 3], vdesc0 + sb2 * 2048 + ks * 128, 1);
          wg_commit();
          CY2(5, wg_wait<1>());
          release(sa);
          CY2(5, wg_wait<0>());
          release(sb2);
          reg_fence(acc); reg_fence_u(p); reg_fence_u(pa);
          const int set = c & 1, use = item * 2 + (c >> 1);
          CY2(4, if (use > 0) mbar_wait(bar_sfree + 8 * (2 * wg + set), (use - 1) & 1));
          const int ln = opaque(lane);
          const uint32_t buf = (set == 0 ? qb_w : qa_w) + ww * 2048;
          stsm_block64(buf, acc, 0, ln);
          stsm_block64(buf + 16384, acc, 8, ln);
          __syncwarp();
          if (lane == 0) mbar_arrive(bar_staged + 8 * (2 * wg + set));
        }
      }
      if (tid == 128) { if (item == 0) TS(1, 5); else TSX(1, 9); }
    }
    if (tid == 128) { TS(1, 1); TS_OUT(1); }
    CYC_OUT(wg);
    CY2_OUT(warp);
    cluster_sync_all();
  }
}

constexpr int T12_A = 0;
constexpr int T12_B = 65536;
constexpr int T12_Y = T12_B + 131072;
constexpr int T12_O = T12_Y + 16384;
constexpr int T12_BAR = T12_O + 16384;
constexpr int T12_R2 = T12_BAR + 128;
constexpr int T12_SMEM = T12_R2 + 256;

__device__ __forceinline__ uint32_t mapa_u32(uint32_t addr, uint32_t cta) {
  uint32_t r;
  asm("mapa.shared::cluster.u32 %0, %1, %2;" : "=r"(r) : "r"(addr), "r"(cta));
  return r;
}

template <int MODE>
__global__ void __launch_bounds__(MODE == 1 ? 512 : 256, 1)
k_t12(const __grid_constant__ CUtensorMap tm_w, const __grid_constant__ CUtensorMap tm_a,
      const __grid_constant__ CUtensorMap tm_y, const __grid_constant__ CUtensorMap tm_o, const bf16* __restrict__ x) {
  extern __shared__ __align__(1024) uint8_t smem[];
  const uint32_t sb = smem_u32(smem);
  const uint32_t bar = sb + T12_BAR;
  const int tid = threadIdx.x, warp = __shfl_sync(0xffffffffu, tid >> 5, 0), lane = tid & 31;
  const int rb = blockIdx.x >> 2, cs = blockIdx.x & 3;
  const int row0 = rb * 64;
  TS_DECL;
  pdl_launch_dependents();
  if (tid == 0) {
    TS(1 + MODE, 0);
    for (int i = 0; i < 6; i++) mbar_init(bar + 8 * i, 1);
    asm volatile("fence.mbarrier_init.release.cluster;" ::: "memory");
    if (MODE == 1) {
      mbar_expect_tx(bar + 40, 32768);
      asm volatile("cp.async.bulk.shared::cluster.global.mbarrier::complete_tx::bytes [%0], [%1], 32768, [%2];"
                   ::"r"(sb + T12_Y), "l"(x + (size_t)(row0 + (blockIdx.x & 1) * 32) * DM), "r"(bar + 40) : "memory");
    }
    for (int kc = 0; kc < 4; kc++) {
      mbar_expect_tx(bar + 8 * kc, MODE == 1 ? 32768 : 49152);
      tma_load_2d(sb + T12_B + kc * 32768, &tm_w, cs * 128, kc * 128, bar + 8 * kc);
      tma_load_2d(sb + T12_B + kc * 32768 + 16384, &tm_w, cs * 128 + 64, kc * 128, bar + 8 * kc);
    }
  }
  if (MODE == 1) {
    if (tid == 0) mbar_expect_tx(bar + 32, 32768 + 128);
    __syncthreads();
    cluster_arrive();
  }
  if (MODE == 1) {
    if (tid == 0) flag_wait(&g_cnth[rb], 16);
    __syncthreads();
  } else {
    pdl_wait();
  }
  if (tid == 0) TS(1 + MODE, 2);
  if (MODE == 2 && tid == 0) {
    for (int kc = 0; kc < 4; kc++) {
      const int sh = (kc == 0) ? -1 : (kc == 1) ? 1 : (kc == 2) ? -2 : 2;
      tma_load_2d(sb + T12_A + (2 * kc) * 8192, &tm_a, kc * 128, row0 + sh, bar + 8 * kc);
      tma_load_2d(sb + T12_A + (2 * kc + 1) * 8192, &tm_a, kc * 128 + 64, row0 + sh, bar + 8 * kc);
    }
    mbar_expect_tx(bar + 32, 16384);
    tma_load_2d(sb + T12_Y, &tm_y, cs * 128, row0, bar + 32);
    tma_load_2d(sb + T12_Y + 8192, &tm_y, cs * 128 + 64, row0, bar + 32);
  }
  if (MODE == 1) {
    const int rank = blockIdx.x & 1;
    float v[2][16];
    {
      uint4 u[2][NBUF + 1][2];
#pragma unroll
      for (int rr = 0; rr < 2; rr++) {
        const size_t row = row0 + rank * 32 + warp * 2 + rr;
#pragma unroll
        for (int b = 0; b < NBUF; b++) {
          const uint4* src = reinterpret_cast<const uint4*>(g_hp + ((size_t)b * SEQ + row) * DM);
          u[rr][b][0] = __ldcg(src + lane);
          u[rr][b][1] = __ldcg(src + 32 + lane);
        }
      }
      mbar_wait(bar + 40, 0);
#pragma unroll
      for (int rr = 0; rr < 2; rr++)
#pragma unroll
        for (int i = 0; i < 2; i++)
          asm volatile("ld.shared.v4.b32 {%0, %1, %2, %3}, [%4];"
                       : "=r"(u[rr][NBUF][i].x), "=r"(u[rr][NBUF][i].y), "=r"(u[rr][NBUF][i].z), "=r"(u[rr][NBUF][i].w)
                       : "r"(sb + T12_Y + (warp * 2 + rr) * 1024 + i * 512 + lane * 16));
#pragma unroll
      for (int rr = 0; rr < 2; rr++)
#pragma unroll
        for (int i = 0; i < 2; i++) {
#pragma unroll
          for (int e = 0; e < 8; e++) v[rr][8 * i + e] = 0.f;
#pragma unroll
          for (int b = 0; b <= NBUF; b++) {
            const uint32_t w[4] = {u[rr][b][i].x, u[rr][b][i].y, u[rr][b][i].z, u[rr][b][i].w};
#pragma unroll
            for (int e = 0; e < 4; e++) { v[rr][8 * i + 2 * e] += bf_lo(w[e]); v[rr][8 * i + 2 * e + 1] += bf_hi(w[e]); }
          }
        }
    }
    uint4 hb[2];
#pragma unroll
    for (int rr = 0; rr < 2; rr++) {
      uint32_t w[4];
#pragma unroll
      for (int e = 0; e < 4; e++)
        w[e] = cs < 2 ? pack_bf16(v[rr][2 * e], v[rr][2 * e + 1]) : pack_bf16(v[rr][8 + 2 * e], v[rr][8 + 2 * e + 1]);
      hb[rr] = make_uint4(w[0], w[1], w[2], w[3]);
    }
    cluster_wait();
    const uint32_t sb_peer = mapa_u32(sb, rank ^ 1), bar_peer = mapa_u32(bar + 32, rank ^ 1);
    float d[2], q[2];
#pragma unroll
    for (int rr = 0; rr < 2; rr++) {
      const float pivot = __shfl_sync(0xffffffffu, v[rr][0], 0);
      d[rr] = 0.f; q[rr] = 0.f;
#pragma unroll
      for (int i = 0; i < 16; i++) { v[rr][i] -= pivot; d[rr] += v[rr][i]; q[rr] = fmaf(v[rr][i], v[rr][i], q[rr]); }
    }
#pragma unroll
    for (int o = 16; o; o >>= 1) {
#pragma unroll
      for (int rr = 0; rr < 2; rr++) {
        d[rr] += __shfl_xor_sync(0xffffffffu, d[rr], o);
        q[rr] += __shfl_xor_sync(0xffffffffu, q[rr], o);
      }
    }
#pragma unroll
    for (int rr = 0; rr < 2; rr++) {
      const int r = rank * 32 + warp * 2 + rr;
      const float mean = d[rr] * (1.f / 512.f);
      const float var = fmaxf(q[rr] * (1.f / 512.f) - mean * mean, 0.f);
      const float r1 = rsqrtf(var + 1e-5f);
      const float nb = -mean * r1;
#pragma unroll
      for (int i = 0; i < 2; i++) {
        const uint32_t off = T12_A + (4 * i + (lane >> 3)) * 8192 + r * 128 + (((lane & 7) ^ (r & 7)) << 4);
        const uint32_t w0 = pack_bf16(fmaf(v[rr][8 * i], r1, nb), fmaf(v[rr][8 * i + 1], r1, nb));
        const uint32_t w1 = pack_bf16(fmaf(v[rr][8 * i + 2], r1, nb), fmaf(v[rr][8 * i + 3], r1, nb));
        const uint32_t w2 = pack_bf16(fmaf(v[rr][8 * i + 4], r1, nb), fmaf(v[rr][8 * i + 5], r1, nb));
        const uint32_t w3 = pack_bf16(fmaf(v[rr][8 * i + 6], r1, nb), fmaf(v[rr][8 * i + 7], r1, nb));
        asm volatile("st.shared.v4.b32 [%0], {%1, %2, %3, %4};" ::"r"(sb + off), "r"(w0), "r"(w1), "r"(w2), "r"(w3) : "memory");
        asm volatile("st.async.weak.shared::cluster.mbarrier::complete_tx::bytes.v4.b32 [%0], {%1, %2, %3, %4}, [%5];"
                     ::"r"(sb_peer + off), "r"(w0), "r"(w1), "r"(w2), "r"(w3), "r"(bar_peer) : "memory");
      }
      if (lane == 0) {
        const float r2 = rsqrtf(var * r1 * r1 + 1e-5f);
        asm volatile("st.shared.f32 [%0], %1;" ::"r"(sb + T12_R2 + r * 4), "f"(r2) : "memory");
        asm volatile("st.async.weak.shared::cluster.mbarrier::complete_tx::bytes.b32 [%0], %1, [%2];"
                     ::"r"(sb_peer + T12_R2 + r * 4), "r"(__float_as_uint(r2)), "r"(bar_peer) : "memory");
      }
    }
    if (tid == 0) TS(2, 6);
    fence_async_smem();
    __syncthreads();
    if (tid == 0) TS(2, 7);
#pragma unroll
    for (int rr = 0; rr < 2; rr++)
      *reinterpret_cast<uint4*>(g_h + (size_t)(row0 + rank * 32 + warp * 2 + rr) * DM + (cs >> 1) * 256 + 8 * lane) = hb[rr];
    mbar_wait(bar + 32, 0);
    fence_async_smem();
    if (tid == 256) {
      tma_store_2d(&tm_y, sb + T12_A + (2 * cs) * 8192, cs * 128, row0);
      tma_store_2d(&tm_y, sb + T12_A + (2 * cs + 1) * 8192, cs * 128 + 64, row0);
      bulk_commit();
      bulk_wait<0>();
    }
  } else {
    __syncthreads();
  }
  if (tid == 0) TS(1 + MODE, 3);
  if (warp >= 8) { if (MODE == 1) { pdl_wait(); __syncwarp(); cluster_sync_all(); } return; }
  const int wg = warp >> 2, ww = warp & 3;
  float acc[32];
#pragma unroll
  for (int kc = 0; kc < 4; kc++) {
    mbar_wait(bar + 8 * kc, 0);
    wg_fence();
#pragma unroll
    for (int ks = 0; ks < 8; ks++)
      wgmma_ss_n64_tb1(acc, desc_k(sb + T12_A) + (2 * kc + (ks >> 2)) * 512 + (ks & 3) * 2,
                       desc_mn(sb + T12_B, 16384) + kc * 2048 + wg * 1024 + ks * 128, (kc | ks) != 0);
    wg_commit();
  }
  wg_wait<0>();
  reg_fence(acc);
  if (tid == 0) TS(1 + MODE, 4);
  const uint32_t stg = sb + T12_O + warp * 2048;
  if (MODE == 1) {
    float r2a, r2b;
    asm volatile("ld.shared.f32 %0, [%1];" : "=f"(r2a) : "r"(sb + T12_R2 + (ww * 16 + (lane >> 2)) * 4));
    asm volatile("ld.shared.f32 %0, [%1];" : "=f"(r2b) : "r"(sb + T12_R2 + (ww * 16 + (lane >> 2) + 8) * 4));
    const GeluRow g0(r2a), g1(r2b);
#pragma unroll
    for (int j = 0; j < 8; j++) {
      acc[4 * j] = g0(acc[4 * j]); acc[4 * j + 1] = g0(acc[4 * j + 1]);
      acc[4 * j + 2] = g1(acc[4 * j + 2]); acc[4 * j + 3] = g1(acc[4 * j + 3]);
    }
  } else {
    mbar_wait(bar + 32, 0);
    const int row = (lane & 7) + ((lane >> 3) & 1) * 8;
    const uint32_t yb = sb + T12_Y + wg * 8192 + (ww * 16 + row) * 128;
    float s0 = 0.f, q0 = 0.f, s1 = 0.f, q1 = 0.f;
#pragma unroll
    for (int j = 0; j < 4; j++) {
      uint32_t y[4];
      asm volatile("ldmatrix.sync.aligned.m8n8.x4.shared.b16 {%0, %1, %2, %3}, [%4];"
                   : "=r"(y[0]), "=r"(y[1]), "=r"(y[2]), "=r"(y[3]) : "r"(yb + (((2 * j + (lane >> 4)) ^ (lane & 7)) << 4)) : "memory");
#pragma unroll
      for (int e = 0; e < 4; e++) {
        const uint32_t a = pack_bf16(bf_lo(y[e]) + acc[8 * j + 2 * e], bf_hi(y[e]) + acc[8 * j + 2 * e + 1]);
        const float lo = bf_lo(a), hi = bf_hi(a);
        acc[8 * j + 2 * e] = lo; acc[8 * j + 2 * e + 1] = hi;
        if (e & 1) { s1 += lo + hi; q1 = fmaf(lo, lo, fmaf(hi, hi, q1)); }
        else { s0 += lo + hi; q0 = fmaf(lo, lo, fmaf(hi, hi, q0)); }
      }
    }
#pragma unroll
    for (int o = 1; o < 4; o <<= 1) {
      s0 += __shfl_xor_sync(0xffffffffu, s0, o); q0 += __shfl_xor_sync(0xffffffffu, q0, o);
      s1 += __shfl_xor_sync(0xffffffffu, s1, o); q1 += __shfl_xor_sync(0xffffffffu, q1, o);
    }
    if ((lane & 3) == 0) {
      const int r0 = row0 + ww * 16 + (lane >> 2);
      g_st[(cs * 2 + wg) * SEQ + r0] = make_float2(s0, q0);
      g_st[(cs * 2 + wg) * SEQ + r0 + 8] = make_float2(s1, q1);
    }
  }
  stsm_block64(stg, acc, 0, lane);
  fence_async_smem();
  __syncwarp();
  if (lane == 0) {
    tma_store_2d(&tm_o, stg, cs * 128 + wg * 64, row0 + ww * 16);
    bulk_commit();
    bulk_wait<0>();
  }
  if (tid == 0) { TS(1 + MODE, 1); TS_OUT(1 + MODE); }
  if (MODE == 1) {
    pdl_wait();
    __syncwarp();
    cluster_sync_all();
  }
}

constexpr int T3_NS = 4;
constexpr int T3_SLOT = 49152;
constexpr int T3_CS = T3_NS * T3_SLOT;
constexpr int T3_BAR = T3_CS + 1024;
constexpr int T3_SMEM = T3_BAR + 256;

__global__ void __launch_bounds__(288, 1)
k_t3(const __grid_constant__ CUtensorMap tm_w3, const __grid_constant__ CUtensorMap tm_x1,
     const __grid_constant__ CUtensorMap tm_gst, const __grid_constant__ CUtensorMap tm_gst32) {
  extern __shared__ __align__(1024) uint8_t smem[];
  const uint32_t sb = smem_u32(smem);
  const uint32_t bar_full = sb + T3_BAR, bar_empty = bar_full + 8 * T3_NS;
  const int tid = threadIdx.x, warp = __shfl_sync(0xffffffffu, tid >> 5, 0), lane = tid & 31;
  const int rank = blockIdx.x & 1, q = blockIdx.x >> 1;
  const int rb = 2 * (q >> 3) + rank, cs = q & 7;
  const int row0 = rb * 128;
  TS_DECL;
  pdl_launch_dependents();
  if (tid == 0) {
    TS(4, 0);
    for (int i = 0; i < T3_NS; i++) { mbar_init(bar_full + 8 * i, 1); mbar_init(bar_empty + 8 * i, 16); }
    asm volatile("fence.mbarrier_init.release.cluster;" ::: "memory");
  }
  __syncthreads();
  cluster_sync_all();
  if (warp == 8) {
    if (lane == 0) {
      auto load_w = [&](int slot, int kb) {
        mbar_expect_tx(bar_full + 8 * slot, T3_SLOT);
#pragma unroll
        for (int b = 0; b < 2; b++)
          tma_load_2d_mc(sb + slot * T3_SLOT + 16384 + (2 * rank + b) * 8192, &tm_w3, cs * 224 + (2 * rank + b) * 64, kb * 64,
                         bar_full + 8 * slot, (uint16_t)3);
      };
      for (int kb = 0; kb < T3_NS; kb++) load_w(kb, kb);
      pdl_wait();
      int slot = 0; uint32_t ph = 0;
      for (int kb = T3_NS; kb < 8; kb++) {
        mbar_wait(bar_empty + 8 * slot, ph);
        load_w(slot, kb);
        tma_load_2d(sb + slot * T3_SLOT, &tm_x1, kb * 64, row0, bar_full + 8 * slot);
        if (++slot == T3_NS) { slot = 0; ph ^= 1; }
      }
    }
    __syncwarp();
  } else {
    const int wg = warp >> 2, ww = warp & 3;
    const int r0 = row0 + wg * 64 + ww * 16 + (lane >> 2);
    pdl_wait();
    if (lane == 0 && warp < T3_NS) tma_load_2d(sb + warp * T3_SLOT, &tm_x1, warp * 64, row0, bar_full + 8 * warp);
    if (tid == 0) TS(4, 2);
    float csv = 0.f;
    float2 sta[2], stb[2];
    if (tid < 224) asm volatile("ld.global.cg.f32 %0, [%1];" : "=f"(csv) : "l"(g_cs3 + cs * 224 + tid));
#pragma unroll
    for (int hf = 0; hf < 2; hf++) {
      asm volatile("ld.global.cg.v2.f32 {%0, %1}, [%2];" : "=f"(sta[hf].x), "=f"(sta[hf].y) : "l"(g_st + (2 * (lane & 3)) * SEQ + r0 + 8 * hf));
      asm volatile("ld.global.cg.v2.f32 {%0, %1}, [%2];" : "=f"(stb[hf].x), "=f"(stb[hf].y) : "l"(g_st + (2 * (lane & 3) + 1) * SEQ + r0 + 8 * hf));
    }
    float acc[112];
    int slot = 0; uint32_t ph = 0; int prev = 0;
    for (int kb = 0; kb < 8; kb++) {
      mbar_wait(bar_full + 8 * slot, ph);
      if (tid == 0 && kb == 0) TS(4, 3);
      wg_fence();
#pragma unroll
      for (int ks = 0; ks < 4; ks++)
        wgmma_ss_n224_tb1(acc, desc_k(sb) + slot * (T3_SLOT / 16) + wg * 512 + ks * 2,
                          desc_mn(sb + 16384, 8192) + slot * (T3_SLOT / 16) + ks * 128, (kb | ks) != 0);
      wg_commit();
      if (kb == 4) {
        if (tid < 224) asm volatile("st.shared.f32 [%0], %1;" ::"r"(sb + T3_CS + tid * 4), "f"(csv) : "memory");
        named_sync(1, 256);
      }
      if (kb > 0) { wg_wait<1>(); if (lane < 2) mbar_arrive_remote(bar_empty + 8 * prev, lane); }
      prev = slot;
      if (++slot == T3_NS) { slot = 0; ph ^= 1; }
    }
    float ra[2], nm[2];
#pragma unroll
    for (int hf = 0; hf < 2; hf++) {
      float s = sta[hf].x + stb[hf].x, qq = sta[hf].y + stb[hf].y;
#pragma unroll
      for (int o = 1; o < 4; o <<= 1) { s += __shfl_xor_sync(0xffffffffu, s, o); qq += __shfl_xor_sync(0xffffffffu, qq, o); }
      const float mean = s * (1.f / 512.f);
      const float var = fmaxf(qq * (1.f / 512.f) - mean * mean, 0.f);
      ra[hf] = rsqrtf(var + 1e-5f);
      nm[hf] = -mean;
    }
    const GeluRow g0(ra[0]), g1(ra[1]);
    wg_wait<0>();
    reg_fence(acc);
    if (tid == 0) TS(4, 4);
    named_sync(1, 256);
    const uint32_t stg = sb + warp * 8192;
    const int grow = row0 + wg * 64 + ww * 16;
    auto gelu_tile = [&](int j) {
      float2 cw;
      asm volatile("ld.shared.v2.f32 {%0, %1}, [%2];" : "=f"(cw.x), "=f"(cw.y) : "r"(sb + T3_CS + ((lane & 3) * 2 + 8 * j) * 4));
      acc[4 * j] = g0(fmaf(nm[0], cw.x, acc[4 * j]));
      acc[4 * j + 1] = g0(fmaf(nm[0], cw.y, acc[4 * j + 1]));
      acc[4 * j + 2] = g1(fmaf(nm[1], cw.x, acc[4 * j + 2]));
      acc[4 * j + 3] = g1(fmaf(nm[1], cw.y, acc[4 * j + 3]));
    };
#pragma unroll
    for (int b = 0; b < 3; b++) {
#pragma unroll
      for (int j = 0; j < 8; j++) gelu_tile(8 * b + j);
      stsm_block64(stg + b * 2048, acc, 8 * b, lane);
      fence_async_smem();
      __syncwarp();
      if (lane == 0) { tma_store_2d(&tm_gst, stg + b * 2048, cs * 224 + b * 64, grow); bulk_commit(); }
    }
    {
#pragma unroll
      for (int j = 24; j < 28; j++) gelu_tile(j);
      const int row = (lane & 7) + ((lane >> 3) & 1) * 8;
#pragma unroll
      for (int j = 0; j < 2; j++) {
        const int t = 24 + 2 * j;
        const uint32_t ad = stg + 6144 + row * 64 + (((2 * j + (lane >> 4)) ^ ((row >> 1) & 3)) << 4);
        stsm_x4(ad, pack_bf16(acc[4 * t], acc[4 * t + 1]), pack_bf16(acc[4 * t + 2], acc[4 * t + 3]),
                pack_bf16(acc[4 * t + 4], acc[4 * t + 5]), pack_bf16(acc[4 * t + 6], acc[4 * t + 7]));
      }
      fence_async_smem();
      __syncwarp();
      if (lane == 0) { tma_store_2d(&tm_gst32, stg + 6144, cs * 224 + 192, grow); bulk_commit(); }
    }
    if (lane == 0) bulk_wait<0>();
    __syncwarp();
    if (tid == 0) { TS(4, 1); TS_OUT(4); }
  }
  cluster_sync_all();
}

constexpr int T4_NS = 8;
constexpr int T4_SLOT = 24576;
constexpr int T4_O = T4_NS * T4_SLOT;
constexpr int T4_BAR = T4_O + 16384;
constexpr int T4_SMEM = T4_BAR + 256;

__global__ void __launch_bounds__(288, 1)
k_t4(const __grid_constant__ CUtensorMap tm_g, const __grid_constant__ CUtensorMap tm_w4, const __grid_constant__ CUtensorMap tm_out,
     const __grid_constant__ CUtensorMap tm_hld, const __grid_constant__ CUtensorMap tm_x1) {
  extern __shared__ __align__(1024) uint8_t smem[];
  const uint32_t sb = smem_u32(smem);
  const uint32_t bar_full = sb + T4_BAR, bar_empty = bar_full + 8 * T4_NS;
  const int tid = threadIdx.x, warp = __shfl_sync(0xffffffffu, tid >> 5, 0), lane = tid & 31;
  const int rank = blockIdx.x & 1;
  const int rb = blockIdx.x >> 3, cs = blockIdx.x & 7;
  const int row0 = rb * 128;
  TS_DECL;
  pdl_launch_dependents();
  if (tid == 0) {
    TS(5, 0);
    for (int i = 0; i < T4_NS; i++) { mbar_init(bar_full + 8 * i, 1); mbar_init(bar_empty + 8 * i, 16); }
    asm volatile("fence.mbarrier_init.release.cluster;" ::: "memory");
  }
  __syncthreads();
  cluster_sync_all();
  if (warp == 8) {
    if (lane == 0) {
      for (int kb = 0; kb < T4_NS; kb++) {
        mbar_expect_tx(bar_full + 8 * kb, T4_SLOT);
        tma_load_2d(sb + kb * T4_SLOT + 16384, &tm_w4, cs * 64, kb * 64, bar_full + 8 * kb);
      }
      pdl_wait();
      int slot = 0; uint32_t ph = 1;
      for (int kb = 0; kb < 28; kb++) {
        if (kb >= T4_NS) {
          mbar_wait(bar_empty + 8 * slot, ph);
          mbar_expect_tx(bar_full + 8 * slot, T4_SLOT);
          tma_load_2d(sb + slot * T4_SLOT + 16384, &tm_w4, cs * 64, kb * 64, bar_full + 8 * slot);
        }
        tma_load_2d_mc(sb + slot * T4_SLOT + rank * 8192, &tm_g, kb * 64, row0 + rank * 64, bar_full + 8 * slot, (uint16_t)3);
        if (++slot == T4_NS) { slot = 0; ph ^= 1; }
      }
      for (int e = 0; e < 2; e++) {
        mbar_wait(bar_empty + 8 * slot, ph);
        mbar_expect_tx(bar_full + 8 * slot, 16384);
        tma_load_2d(sb + slot * T4_SLOT, e == 0 ? &tm_hld : &tm_x1, cs * 64, row0, bar_full + 8 * slot);
        if (++slot == T4_NS) { slot = 0; ph ^= 1; }
      }
    }
    __syncwarp();
  } else {
    const int wg = warp >> 2, ww = warp & 3;
    if (tid == 0) TS(5, 2);
    float acc[32];
    int slot = 0; uint32_t ph = 0; int prev = 0;
    for (int kb = 0; kb < 28; kb++) {
      mbar_wait(bar_full + 8 * slot, ph);
      if (tid == 0 && kb == 0) TS(5, 3);
      wg_fence();
#pragma unroll
      for (int ks = 0; ks < 4; ks++)
        wgmma_ss_n64_tb1(acc, desc_k(sb) + slot * (T4_SLOT / 16) + wg * 512 + ks * 2,
                         desc_mn(sb + 16384, 8192) + slot * (T4_SLOT / 16) + ks * 128, (kb | ks) != 0);
      wg_commit();
      if (kb > 0) { wg_wait<1>(); if (lane < 2) mbar_arrive_remote(bar_empty + 8 * prev, lane); }
      prev = slot;
      if (++slot == T4_NS) { slot = 0; ph ^= 1; }
    }
    wg_wait<0>();
    reg_fence(acc);
    if (lane < 2) mbar_arrive_remote(bar_empty + 8 * prev, lane);
    if (tid == 0) TS(5, 4);
    {
      const int row = (lane & 7) + ((lane >> 3) & 1) * 8;
#pragma unroll
      for (int t = 0; t < 2; t++) {
        mbar_wait(bar_full + 8 * (4 + t), 1);
        const uint32_t xb = sb + (4 + t) * T4_SLOT + (wg * 64 + ww * 16 + row) * 128;
#pragma unroll
        for (int j = 0; j < 4; j++) {
          uint32_t y[4];
          asm volatile("ldmatrix.sync.aligned.m8n8.x4.shared.b16 {%0, %1, %2, %3}, [%4];"
                       : "=r"(y[0]), "=r"(y[1]), "=r"(y[2]), "=r"(y[3]) : "r"(xb + (((2 * j + (lane >> 4)) ^ (lane & 7)) << 4)) : "memory");
#pragma unroll
          for (int e = 0; e < 4; e++) { acc[8 * j + 2 * e] += bf_lo(y[e]); acc[8 * j + 2 * e + 1] += bf_hi(y[e]); }
        }
      }
    }
    const uint32_t stg = sb + T4_O + warp * 2048;
    stsm_block64(stg, acc, 0, lane);
    fence_async_smem();
    __syncwarp();
    if (lane == 0) {
      tma_store_2d(&tm_out, stg, cs * 64, row0 + wg * 64 + ww * 16);
      bulk_commit();
      bulk_wait<0>();
    }
    __syncwarp();
    if (tid == 0) { TS(5, 1); TS_OUT(5); }
  }
  cluster_sync_all();
}

typedef CUresult (*EncodeFn)(CUtensorMap*, CUtensorMapDataType, cuuint32_t, void*, const cuuint64_t*, const cuuint64_t*,
                             const cuuint32_t*, const cuuint32_t*, CUtensorMapInterleave, CUtensorMapSwizzle,
                             CUtensorMapL2promotion, CUtensorMapFloatOOBfill);

static void make_map(EncodeFn enc, CUtensorMap* tm, const void* ptr, bool f32, uint64_t cols, uint64_t rows, uint32_t bc, uint32_t br,
                     CUtensorMapSwizzle sw = CU_TENSOR_MAP_SWIZZLE_128B) {
  cuuint64_t gd[2] = {cols, rows};
  cuuint64_t gs[1] = {cols * (f32 ? 4 : 2)};
  cuuint32_t bd[2] = {bc, br};
  cuuint32_t es[2] = {1, 1};
  enc(tm, f32 ? CU_TENSOR_MAP_DATA_TYPE_FLOAT32 : CU_TENSOR_MAP_DATA_TYPE_BFLOAT16, 2, const_cast<void*>(ptr), gd, gs, bd, es,
      CU_TENSOR_MAP_INTERLEAVE_NONE, sw, CU_TENSOR_MAP_L2_PROMOTION_L2_128B, CU_TENSOR_MAP_FLOAT_OOB_FILL_NONE);
}

struct Maps {
  CUtensorMap ckv, wuk, wuv, kvst, xn0, xn1, wq, kv, wo, h, w1, w2, h1, h1st, y, x1st, w3, x1, gst, gst32, g, w4, out, hld;
  const void* key[12];
  bool valid;
};

template <typename... KArgs, typename... Args>
static void launch(void (*kern)(KArgs...), int threads, int smem, int cluster, bool pdl, Args... args) {
  cudaLaunchConfig_t cfg = {};
  cfg.gridDim = dim3(128); cfg.blockDim = dim3(threads); cfg.dynamicSmemBytes = smem; cfg.stream = cudaStreamPerThread;
  cudaLaunchAttribute at[2];
  int n = 0;
  if (cluster > 1) {
    at[n].id = cudaLaunchAttributeClusterDimension;
    at[n].val.clusterDim.x = cluster; at[n].val.clusterDim.y = 1; at[n].val.clusterDim.z = 1;
    n++;
  }
  if (pdl) {
    at[n].id = cudaLaunchAttributeProgrammaticStreamSerialization;
    at[n].val.programmaticStreamSerializationAllowed = 1;
    n++;
  }
  cfg.attrs = at; cfg.numAttrs = n;
  cudaLaunchKernelEx(&cfg, kern, args...);
}

extern "C" void kernel_launch(void* const* d_in, const int* in_sizes, int n_in, void* d_out, int out_size) {
  const bf16* x = (const bf16*)d_in[0];
  static Maps M;
  static EncodeFn enc = nullptr;
  if (!enc) {
    void* fn = nullptr;
    cudaDriverEntryPointQueryResult qr;
    cudaGetDriverEntryPoint("cuTensorMapEncodeTiled", &fn, cudaEnableDefault, &qr);
    enc = (EncodeFn)fn;
    cudaFuncSetAttribute(k_p1, cudaFuncAttributeMaxDynamicSharedMemorySize, P1_SMEM);
    cudaFuncSetAttribute(k_p2, cudaFuncAttributeMaxDynamicSharedMemorySize, P2_SMEM);
    cudaFuncSetAttribute(k_t12<1>, cudaFuncAttributeMaxDynamicSharedMemorySize, T12_SMEM);
    cudaFuncSetAttribute(k_t12<2>, cudaFuncAttributeMaxDynamicSharedMemorySize, T12_SMEM);
    cudaFuncSetAttribute(k_t3, cudaFuncAttributeMaxDynamicSharedMemorySize, T3_SMEM);
    cudaFuncSetAttribute(k_t4, cudaFuncAttributeMaxDynamicSharedMemorySize, T4_SMEM);
  }
  bool same = M.valid && M.key[11] == d_out;
  for (int i = 0; i < 11 && same; i++) same = (M.key[i] == d_in[i]);
  if (!same) {
    void *p_xn, *p_kv, *p_h, *p_hp, *p_h1, *p_g, *p_x1, *p_y;
    cudaGetSymbolAddress(&p_hp, g_hp);
    cudaGetSymbolAddress(&p_y, g_y);
    cudaGetSymbolAddress(&p_xn, g_xn); cudaGetSymbolAddress(&p_kv, g_kv); cudaGetSymbolAddress(&p_h, g_h);
    cudaGetSymbolAddress(&p_h1, g_h1); cudaGetSymbolAddress(&p_g, g_g); cudaGetSymbolAddress(&p_x1, g_x1);
    make_map(enc, &M.ckv, d_in[1], false, DM, SEQ, 64, 128);
    make_map(enc, &M.wuk, d_in[3], false, NH * HD, DM, 64, 64);
    make_map(enc, &M.wuv, d_in[4], false, NH * HD, DM, 64, 64);
    make_map(enc, &M.kvst, p_kv, false, HD, 2 * NH * SEQ, 64, 16);
    for (int r = 0; r < 2; r++) {
      cuuint64_t gd[4] = {64, 64, 32, 8};
      cuuint64_t gs[3] = {DM * 2, 64 * DM * 2, 128};
      cuuint32_t bd[4] = {64, 64, (cuuint32_t)(r == 0 ? 4 : 2), 2};
      cuuint32_t es[4] = {1, 1, (cuuint32_t)(r == 0 ? 3 : 1), 1};
      CUresult rc = enc(r == 0 ? &M.xn0 : &M.xn1, CU_TENSOR_MAP_DATA_TYPE_BFLOAT16, 4, p_xn, gd, gs, bd, es, CU_TENSOR_MAP_INTERLEAVE_NONE,
          CU_TENSOR_MAP_SWIZZLE_128B, CU_TENSOR_MAP_L2_PROMOTION_L2_128B, CU_TENSOR_MAP_FLOAT_OOB_FILL_NONE);
      (void)rc;
    }
    {
      cuuint64_t gd[3] = {64, DM, 64};
      cuuint64_t gs[2] = {NH * HD * 2, 128};
      cuuint32_t bd[3] = {64, 64, 2};
      cuuint32_t es[3] = {1, 1, 1};
      enc(&M.wq, CU_TENSOR_MAP_DATA_TYPE_BFLOAT16, 3, d_in[2], gd, gs, bd, es, CU_TENSOR_MAP_INTERLEAVE_NONE,
          CU_TENSOR_MAP_SWIZZLE_128B, CU_TENSOR_MAP_L2_PROMOTION_L2_128B, CU_TENSOR_MAP_FLOAT_OOB_FILL_NONE);
    }
    make_map(enc, &M.kv, p_kv, false, HD, 2 * NH * SEQ, 64, 128);
    make_map(enc, &M.wo, d_in[5], false, DM, NH * HD, 64, 128);
    make_map(enc, &M.h, p_hp, false, DM, NBUF * SEQ, 64, 16);
    make_map(enc, &M.hld, p_h, false, DM, SEQ, 64, 128);
    make_map(enc, &M.w1, d_in[7], false, DM, DM, 64, 128);
    make_map(enc, &M.w2, d_in[8], false, DM, DM, 64, 128);
    make_map(enc, &M.h1, p_h1, false, DM, SEQ, 64, 64);
    make_map(enc, &M.h1st, p_h1, false, DM, SEQ, 64, 16);
    make_map(enc, &M.y, p_y, false, DM, SEQ, 64, 64);
    make_map(enc, &M.x1st, p_x1, false, DM, SEQ, 64, 16);
    make_map(enc, &M.gst, p_g, false, FF, SEQ, 64, 16);
    make_map(enc, &M.gst32, p_g, false, FF, SEQ, 32, 16, CU_TENSOR_MAP_SWIZZLE_64B);
    make_map(enc, &M.out, d_out, false, DM, SEQ, 64, 16);
    make_map(enc, &M.w3, d_in[9], false, FF, DM, 64, 64);
    make_map(enc, &M.x1, p_x1, false, DM, SEQ, 64, 128);
    make_map(enc, &M.g, p_g, false, FF, SEQ, 64, 64);
    make_map(enc, &M.w4, d_in[10], false, DM, FF, 64, 64);
    for (int i = 0; i < 11; i++) M.key[i] = d_in[i];
    M.key[11] = d_out;
    M.valid = true;
  }
  launch(k_p1, 384, P1_SMEM, 2, false, M.ckv, M.wuk, M.wuv, M.kvst, x, (const bf16*)d_in[2]);
  launch(k_p2, 384, P2_SMEM, 2, USE_PDL, M.xn0, M.xn1, M.wq, M.kv, M.wo, M.h, x, (const bf16*)d_in[7], (const bf16*)d_in[8],
         (const bf16*)d_in[9], (const bf16*)d_in[10]);
  launch(k_t12<1>, 512, T12_SMEM, 2, USE_PDL, M.w1, M.h1, M.y, M.h1st, x);
  launch(k_t12<2>, 256, T12_SMEM, 1, USE_PDL, M.w2, M.h1, M.y, M.x1st, x);
  launch(k_t3, 288, T3_SMEM, 2, USE_PDL, M.w3, M.x1, M.gst, M.gst32);
  launch(k_t4, 288, T4_SMEM, 2, USE_PDL, M.g, M.w4, M.out, M.hld, M.x1);
}
```
